```python
import torch

def _softmax(x, axis=-1):
    return torch.softmax(x, dim=axis)
def _gelu(x):
    return torch.nn.functional.gelu(x, approximate="tanh")
def _silu(x):
    return torch.nn.functional.silu(x)
def _sigmoid(x):
    return torch.sigmoid(x)
def _layernorm(x, axis=-1, eps=1e-5):
    m = x.mean(dim=axis, keepdim=True)
    v = x.var(dim=axis, keepdim=True, unbiased=False)
    return (x - m) / torch.sqrt(v + eps)
def _scatter_add(tgt, idx, src, axis=0):
    return tgt.clone().index_add_(axis, idx, src)
def _segment_sum(src, seg, n):
    out = torch.zeros((n,) + src.shape[1:], dtype=src.dtype)
    return out.index_add_(0, seg, src)
def _pad(x, pw):
    flat = tuple(v for pair in reversed(pw) for v in pair)
    return torch.nn.functional.pad(x, flat)

kernel_name = 'parallel_sum__ssm_conv_s5__mixer_token_mlp__prompt'

def setup_inputs():

    _w = (lambda a: (lambda t: t.to(torch.bfloat16) if t.is_floating_point() else t)(torch.as_tensor(a)))
    def _A_setup():
        B, S, D = 1, 2048, 448
        P = D
        Lambda_re = -0.5 * (lambda _x: torch.exp(torch.as_tensor(_x)))((lambda *s: torch.randn(*s, dtype=torch.bfloat16) * 0.1)(P))
        Lambda_im = (lambda *s: torch.randn(*s, dtype=torch.bfloat16) * 0.4)(P) * 1.0
        B_re = (lambda *s: torch.randn(*s, dtype=torch.bfloat16) * 0.2)(P, D) * (D ** -0.5)
        B_im = (lambda *s: torch.randn(*s, dtype=torch.bfloat16) * 0.2)(P, D) * (D ** -0.5)
        C_re = (lambda *s: torch.randn(*s, dtype=torch.bfloat16) * 0.2)(D, P) * (P ** -0.5)
        C_im = (lambda *s: torch.randn(*s, dtype=torch.bfloat16) * 0.2)(D, P) * (P ** -0.5)
        log_dt = (lambda *s: torch.randn(*s, dtype=torch.bfloat16) * 0.1)(P) * 0.3 - 2.0
        Dskip = (lambda *s: torch.randn(*s, dtype=torch.bfloat16) * 0.05)(D)
        return {
            "x": _w((lambda *s: torch.randn(*s, dtype=torch.bfloat16) * 0.05)(B, S, D)),
            "Lambda_re": _w(Lambda_re),
            "Lambda_im": _w(Lambda_im),
            "B_re": _w(B_re),
            "B_im": _w(B_im),
            "C_re": _w(C_re),
            "C_im": _w(C_im),
            "log_dt": _w(log_dt),
            "Dskip": _w(Dskip),
        }
    _A_in = _A_setup()

    def _B_setup():
        B, S, D, F = 1, 2048, 448, 1792
        return {
            "x": _w((lambda *s: torch.randn(*s, dtype=torch.bfloat16) * 0.05)(B, S, D)),
            "w1": _w((lambda *s: torch.randn(*s, dtype=torch.bfloat16) * 0.8)(S, F) * (S ** -0.5)),
            "b1": _w((lambda *s: torch.randn(*s, dtype=torch.bfloat16) * 3.2)(F) * 0.02),
            "w2": _w((lambda *s: torch.randn(*s, dtype=torch.bfloat16) * 0.4)(F, S) * (F ** -0.5)),
            "b2": _w((lambda *s: torch.randn(*s, dtype=torch.bfloat16) * 1.6)(S) * 0.02),
        }
    _B_in = _B_setup()

    return {
        "A_x": _A_in["x"],
        "A_Lambda_re": _A_in["Lambda_re"],
        "A_Lambda_im": _A_in["Lambda_im"],
        "A_B_re": _A_in["B_re"],
        "A_B_im": _A_in["B_im"],
        "A_C_re": _A_in["C_re"],
        "A_C_im": _A_in["C_im"],
        "A_log_dt": _A_in["log_dt"],
        "A_Dskip": _A_in["Dskip"],
        "B_x": _B_in["x"],
        "B_w1": _B_in["w1"],
        "B_b1": _B_in["b1"],
        "B_w2": _B_in["w2"],
        "B_b2": _B_in["b2"],
    }

def reference(A_x, A_Lambda_re, A_Lambda_im, A_B_re, A_B_im, A_C_re, A_C_im, A_log_dt, A_Dskip, B_x, B_w1, B_b1, B_w2, B_b2):
    def _A_ref(x, Lambda_re, Lambda_im, B_re, B_im, C_re, C_im, log_dt, Dskip):
        Bsz, L, H = x.shape
        Lam = Lambda_re + 1j * Lambda_im
        Bmat = B_re + 1j * B_im
        Cmat = C_re + 1j * C_im
        dt = torch.exp(log_dt)
        Lam_bar = torch.exp(dt * Lam)
        B_bar = ((Lam_bar - 1.0) / Lam)[:, None] * Bmat
        Bu = torch.einsum("bld,pd->blp", x + 0j, B_bar)
        h = torch.zeros_like(Bu[:, 0, :])
        hs = []
        for t in range(L):
            h = Lam_bar[None, :] * h + Bu[:, t, :]
            hs.append(h)
        hseq = torch.stack(hs, 1)
        y = 2.0 * torch.einsum("blp,dp->bld", hseq, Cmat).real + x * Dskip[None, None, :]
        return y

    def _B_ref(x, w1, b1, w2, b2):
        B, S, D = x.shape
        h = _layernorm(x, axis=-1)
        u = torch.einsum("bsd,sf->bdf", h, w1) + b1
        u = _gelu(u)
        y = torch.einsum("bdf,fs->bds", u, w2) + b2
        return (lambda x, *d: x.permute(*d))(y, 0, 2, 1)

    x = A_x
    xn = _layernorm(x, axis=-1)
    return x + _A_ref(xn, A_Lambda_re, A_Lambda_im, A_B_re, A_B_im, A_C_re, A_C_im, A_log_dt, A_Dskip) + _B_ref(xn, B_w1, B_b1, B_w2, B_b2)
```

```cpp
#include <cuda_runtime.h>
#include <cuda.h>
#include <cuda_bf16.h>
#include <stdint.h>

namespace {

constexpr int S_ = 2048, D_ = 448, F_ = 1792;
constexpr int CS = 16, NCL = 7, NCTA = CS * NCL;
constexpr int NSLOT = 8;
constexpr int SLOT_BYTES = 24576;
constexpr int STAGE_OFF = NSLOT * SLOT_BYTES;
constexpr int AUX_OFF = STAGE_OFF + 32768;
constexpr int SMEM_BYTES = AUX_OFF + 3072;
constexpr int N_G1 = 32, N_CP = 14, N_G2 = 28, N_ALL = N_G1 + N_CP + N_G2;
constexpr int BAR_FULL = AUX_OFF;
constexpr int BAR_PR = AUX_OFF + 592;
constexpr int BAR_ST = AUX_OFF + 600;
constexpr int BAR_G1 = AUX_OFF + 608;
constexpr int BAR_EMPTY = AUX_OFF + 640;
constexpr int BAR_BU = AUX_OFF + 1280;
constexpr int BAR_RDY = BAR_BU + 56;
constexpr int BAR_HS = BAR_EMPTY + 592;
constexpr int BAR_CY = BAR_EMPTY + 600;
constexpr int BAR_P1 = BAR_EMPTY + 608;
constexpr int BAR_RES = BAR_EMPTY + 616;
constexpr int BAR_K6 = BAR_EMPTY + 624;
constexpr int BAR_AUX = BAR_EMPTY + 632;
constexpr int PARAM_OFF = STAGE_OFF + 28672;
constexpr int AUX_STAT = AUX_OFF + 1344;
constexpr int AUX_BSUM = AUX_STAT + 1152;
constexpr int AUX_EPOCH = AUX_BSUM + 512;
constexpr int SPIN_LIMIT = 1 << 22;
#define PF_START 2300
#define PF_PACE 330
#define BU_PACE 480
#define G1_PACE 150
#define GELU_WARM 0
#define QD 1
#define SPIN_NS 0
#define PF2_NS 150
#define H_NS 60
#define LN_WARM 0
#define H_PIECE 4096
#define GATE 1
#define EXP 0
#define DRY 0
#define RELAXPOLL 1
#define POLL_NS 0
#define PF_FIRST 4
#define PF1_NS 100
#define ALU_STATS 0
#define H_LAG 5
#define H_PACE 75

constexpr int CNT_LN = 0, CNT_H = 16, CNT_U = 48, CNT_N = 76;

struct Scratch {
    unsigned cnt[CNT_N * 32];
    unsigned epoch[32 * 4];
    uint4 stat[S_];
    uint2 bsum[2 * D_];
    uint4 fin[16 * D_];
    __nv_bfloat16 hn[S_ * D_];
    __nv_bfloat16 U[F_ * D_];
    __nv_bfloat16 H[S_ * 2 * D_];
};
__device__ __align__(1024) Scratch g_s;
#define PROF_T(k) do { } while (0)
#define PROF_PARM
#define PROF_ARG
#define PROF_E(r, n) do { } while (0)
#define PROF_N(r, n) do { } while (0)

struct Params {
    const __nv_bfloat16 *x, *bre, *bim;
    Scratch* s;
    const __nv_bfloat16 *lre, *lim, *ldt, *w1, *w2, *cre, *cim, *dsk, *b1, *b2;
    float* out;
};

__device__ __forceinline__ uint32_t smem_u32(const void* p) { return (uint32_t)__cvta_generic_to_shared(p); }
__device__ __forceinline__ bool elect_one() {
    uint32_t p;
    asm volatile("{\n.reg .pred P;\nelect.sync _|P, 0xffffffff;\nselp.u32 %0, 1, 0, P;\n}" : "=r"(p));
    return p != 0;
}
__device__ __forceinline__ bool opaque(bool b) {
    uint32_t v = b;
    asm volatile("" : "+r"(v));
    return __shfl_sync(0xffffffffu, v, 0) != 0;
}
__device__ __forceinline__ void mbar_init(uint32_t a, uint32_t cnt) {
    asm volatile("mbarrier.init.shared::cta.b64 [%0], %1;" ::"r"(a), "r"(cnt) : "memory");
}
__device__ __forceinline__ void mbar_expect_tx(uint32_t a, uint32_t bytes) {
    asm volatile("mbarrier.arrive.expect_tx.shared::cta.b64 _, [%0], %1;" ::"r"(a), "r"(bytes) : "memory");
}
__device__ __forceinline__ void mbar_arrive(uint32_t a) {
    asm volatile("mbarrier.arrive.shared::cta.b64 _, [%0];" ::"r"(a) : "memory");
}
__device__ __forceinline__ void mbar_arrive_n(uint32_t a, uint32_t n) {
    asm volatile("mbarrier.arrive.shared::cta.b64 _, [%0], %1;" ::"r"(a), "r"(n) : "memory");
}
template <int N>
__device__ __forceinline__ void init_barriers(uint32_t a, uint32_t cnt) {
    if (elect_one()) {
#pragma unroll
        for (int i = 0; i < N; i++) mbar_init(a + i * 8, cnt);
        asm volatile("fence.mbarrier_init.release.cluster;" ::: "memory");
    }
    __syncwarp();
}
__device__ __forceinline__ void mbar_arrive_cluster(uint32_t ra) {
    asm volatile("mbarrier.arrive.shared::cluster.b64 _, [%0];" ::"r"(ra) : "memory");
}
__device__ __forceinline__ uint32_t mapa(uint32_t a, uint32_t cta) {
    uint32_t r;
    asm volatile("mapa.shared::cluster.u32 %0, %1, %2;" : "=r"(r) : "r"(a), "r"(cta));
    return r;
}
__device__ __forceinline__ bool mbar_try(uint32_t a, uint32_t parity) {
    uint32_t ok;
    asm volatile("{\n.reg .pred p;\nmbarrier.try_wait.parity.shared::cta.b64 p, [%1], %2;\nselp.u32 %0, 1, 0, p;\n}"
                 : "=r"(ok) : "r"(a), "r"(parity) : "memory");
    return ok != 0;
}
__device__ __forceinline__ void mbar_wait(uint32_t a, uint32_t parity) {
    if (__builtin_expect(mbar_try(a, parity), 1)) return;
    int it = 0;
    while (!mbar_try(a, parity)) {
        if (++it > SPIN_LIMIT) __trap();
    }
}
__device__ __forceinline__ bool mbar_test(uint32_t a) {
    uint32_t ok;
    asm volatile("{\n.reg .pred p;\nmbarrier.test_wait.parity.shared::cta.b64 p, [%1], 0;\nselp.u32 %0, 1, 0, p;\n}"
                 : "=r"(ok) : "r"(a) : "memory");
    return ok != 0;
}
__device__ __forceinline__ void mbar_wait0(uint32_t a, uint32_t& spin) {
    asm volatile(
        "{\n.reg .pred p;\n"
        "WAIT_%=:\n"
        "mbarrier.try_wait.parity.shared::cta.b64 p, [%1], 0;\n"
        "@p bra DONE_%=;\n"
        "add.u32 %0, %0, 1;\n"
        "setp.lt.u32 p, %0, %2;\n"
        "@p bra WAIT_%=;\n"
        "trap;\n"
        "DONE_%=:\n}" : "+r"(spin) : "r"(a), "n"(SPIN_LIMIT) : "memory");
}
__device__ __forceinline__ void mbar_wait_cluster(uint32_t a, uint32_t& spin) {
    asm volatile(
        "{\n.reg .pred p;\n"
        "WAIT_%=:\n"
        "mbarrier.try_wait.parity.acquire.cluster.shared::cta.b64 p, [%1], 0;\n"
        "@p bra DONE_%=;\n"
        "add.u32 %0, %0, 1;\n"
        "setp.lt.u32 p, %0, %2;\n"
        "@p bra WAIT_%=;\n"
        "trap;\n"
        "DONE_%=:\n}" : "+r"(spin) : "r"(a), "n"(SPIN_LIMIT) : "memory");
}
__device__ __forceinline__ void tma2d_mc(uint32_t dst, const CUtensorMap* m, int c0, int c1, uint32_t bar, uint16_t mask) {
    asm volatile(
        "cp.async.bulk.tensor.2d.shared::cluster.global.mbarrier::complete_tx::bytes.multicast::cluster"
        " [%0], [%1, {%3, %4}], [%2], %5;" ::"r"(dst), "l"(m), "r"(bar), "r"(c0), "r"(c1), "h"(mask) : "memory");
}
__device__ __forceinline__ void tma3d_mc(uint32_t dst, const CUtensorMap* m, int c0, int c1, int c2, uint32_t bar, uint16_t mask) {
    asm volatile(
        "cp.async.bulk.tensor.3d.shared::cluster.global.mbarrier::complete_tx::bytes.multicast::cluster"
        " [%0], [%1, {%3, %4, %5}], [%2], %6;" ::"r"(dst), "l"(m), "r"(bar), "r"(c0), "r"(c1), "r"(c2), "h"(mask) : "memory");
}
__device__ __forceinline__ void tma5d_mc(uint32_t dst, const CUtensorMap* m, int c0, int c4, uint32_t bar, uint16_t mask) {
    asm volatile(
        "cp.async.bulk.tensor.5d.shared::cluster.global.mbarrier::complete_tx::bytes.multicast::cluster"
        " [%0], [%1, {%3, %6, %6, %6, %4}], [%2], %5;" ::"r"(dst), "l"(m), "r"(bar), "r"(c0), "r"(c4), "h"(mask), "r"(0) : "memory");
}
__device__ __forceinline__ void bulk_mc(uint32_t dst, const void* src, uint32_t bytes, uint32_t bar, uint16_t mask) {
    asm volatile(
        "cp.async.bulk.shared::cluster.global.mbarrier::complete_tx::bytes.multicast::cluster"
        " [%0], [%1], %2, [%3], %4;" ::"r"(dst), "l"(src), "r"(bytes), "r"(bar), "h"(mask) : "memory");
}
__device__ __forceinline__ void bulk_store(void* dst, uint32_t src, uint32_t bytes) {
    asm volatile("cp.async.bulk.global.shared::cta.bulk_group [%0], [%1], %2;" ::"l"(dst), "r"(src), "r"(bytes) : "memory");
}
__device__ __forceinline__ void tma2d_store(const CUtensorMap* m, int c0, int c1, uint32_t src) {
    asm volatile("cp.async.bulk.tensor.2d.global.shared::cta.bulk_group [%0, {%2, %3}], [%1];" ::"l"(m), "r"(src), "r"(c0), "r"(c1) : "memory");
}
__device__ __forceinline__ void bulk_commit() { asm volatile("cp.async.bulk.commit_group;" ::: "memory"); }
__device__ __forceinline__ void bulk_wait_all() { asm volatile("cp.async.bulk.wait_group 0;" ::: "memory"); }
__device__ __forceinline__ void bulk_wait_read() { asm volatile("cp.async.bulk.wait_group.read 0;" ::: "memory"); }
__device__ __forceinline__ void l2_prefetch(const void* p, uint32_t bytes) {
    asm volatile("cp.async.bulk.prefetch.L2.global [%0], %1;" ::"l"(p), "r"(bytes) : "memory");
}
__device__ __forceinline__ void fence_async_smem() { asm volatile("fence.proxy.async.shared::cta;" ::: "memory"); }
__device__ __forceinline__ void fence_async_global() { asm volatile("fence.proxy.async.global;" ::: "memory"); }
__device__ __forceinline__ void cluster_arrive() { asm volatile("barrier.cluster.arrive.relaxed.aligned;" ::: "memory"); }
__device__ __forceinline__ void cluster_wait() { asm volatile("barrier.cluster.wait.aligned;" ::: "memory"); }
__device__ __forceinline__ void wg_bar(int id) { asm volatile("bar.sync %0, 128;" ::"r"(id) : "memory"); }
__device__ __forceinline__ void wg_fence() { asm volatile("wgmma.fence.sync.aligned;" ::: "memory"); }
__device__ __forceinline__ void wg_commit() { asm volatile("wgmma.commit_group.sync.aligned;" ::: "memory"); }
template <int N> __device__ __forceinline__ void wg_wait() { asm volatile("wgmma.wait_group.sync.aligned %0;" ::"n"(N) : "memory"); }
template <int N> __device__ __forceinline__ void pin(float (&d)[N]) {
#pragma unroll
    for (int i = 0; i < N; i++) asm volatile("" : "+f"(d[i])::"memory");
}
__device__ __forceinline__ void cnt_add(unsigned* c) {
    asm volatile("red.release.gpu.global.add.u32 [%0], 1;" ::"l"(c) : "memory");
}
__device__ __forceinline__ void cnt_add_relaxed(unsigned* c) {
    asm volatile("red.relaxed.gpu.global.add.u32 [%0], 1;" ::"l"(c) : "memory");
}
__device__ __forceinline__ void st_ll(uint4* p, float a, float b, unsigned tag) {
    asm volatile("st.relaxed.gpu.global.v4.u32 [%0], {%1, %3, %2, %3};" ::"l"(p), "r"(__float_as_uint(a)), "r"(__float_as_uint(b)), "r"(tag) : "memory");
}
__device__ __forceinline__ void st_v4(void* p, const uint32_t (&v)[4]) {
    asm volatile("st.global.v4.u32 [%0], {%1, %2, %3, %4};" ::"l"(p), "r"(v[0]), "r"(v[1]), "r"(v[2]), "r"(v[3]) : "memory");
}
__device__ __forceinline__ uint4 ld_ll(const void* p) {
    uint4 v;
    asm volatile("ld.relaxed.gpu.global.v4.u32 {%0, %1, %2, %3}, [%4];" : "=r"(v.x), "=r"(v.y), "=r"(v.z), "=r"(v.w) : "l"(p) : "memory");
    return v;
}
__device__ __forceinline__ unsigned ld_relaxed(const unsigned* p) {
    unsigned v;
    asm volatile("ld.relaxed.gpu.global.u32 %0, [%1];" : "=r"(v) : "l"(p) : "memory");
    return v;
}
__device__ __forceinline__ void l2_prefetch_line(const void* p) { asm volatile("prefetch.global.L2 [%0];" ::"l"(p) : "memory"); }
__device__ __forceinline__ void spin_until(long long t) { while (clock64() < t) { if (SPIN_NS) __nanosleep(SPIN_NS); } }
__device__ __forceinline__ unsigned ld_acquire(const unsigned* p) {
    unsigned v;
    asm volatile("ld.acquire.gpu.global.u32 %0, [%1];" : "=r"(v) : "l"(p) : "memory");
    return v;
}
__device__ __forceinline__ unsigned ld_poll(const unsigned* p) { return RELAXPOLL ? ld_relaxed(p) : ld_acquire(p); }
__device__ __forceinline__ void nb_arrive(int id, int n) { asm volatile("bar.arrive %0, %1;" ::"r"(id), "r"(n) : "memory"); }
__device__ __forceinline__ void nb_sync(int id, int n) { asm volatile("bar.sync %0, %1;" ::"r"(id), "r"(n) : "memory"); }
__device__ __forceinline__ void warp_wait_cnt(const unsigned* c0, int n, unsigned target, int lane) {
    const unsigned* p = c0 + (lane < n ? lane : 0) * 32;
    int it = 0;
    while (true) {
        unsigned v = ld_poll(p);
        if (__all_sync(0xffffffffu, (int)(v - target) >= 0)) break;
        if (POLL_NS) __nanosleep(POLL_NS);
        if (++it > SPIN_LIMIT) __trap();
    }
}
__device__ __forceinline__ uint64_t mkdesc(uint32_t addr, uint32_t lbo, uint32_t sbo, uint32_t swz) {
    return (uint64_t)((addr & 0x3FFFF) >> 4) | ((uint64_t)(lbo >> 4) << 16) | ((uint64_t)(sbo >> 4) << 32) | ((uint64_t)swz << 62);
}
__device__ __forceinline__ uint32_t pack_bf16(float lo, float hi) {
    uint32_t r;
    asm("cvt.rn.bf16x2.f32 %0, %1, %2;" : "=r"(r) : "f"(hi), "f"(lo));
    return r;
}
__device__ __forceinline__ float bf_lo(uint32_t v) { return __uint_as_float(v << 16); }
__device__ __forceinline__ float bf_hi(uint32_t v) { return __uint_as_float(v & 0xffff0000u); }
__device__ __forceinline__ float ldbf(const __nv_bfloat16* p) { return __bfloat162float(__ldg(p)); }
__device__ __forceinline__ float2 cmul(float2 a, float2 b) { return make_float2(a.x * b.x - a.y * b.y, a.x * b.y + a.y * b.x); }
__device__ __forceinline__ float2 cfma(float2 a, float2 b, float2 c) {
    return make_float2(fmaf(a.x, b.x, fmaf(-a.y, b.y, c.x)), fmaf(a.x, b.y, fmaf(a.y, b.x, c.y)));
}
__device__ __forceinline__ float2 shfl_up2(float2 v, int d) {
    return make_float2(__shfl_up_sync(0xffffffffu, v.x, d), __shfl_up_sync(0xffffffffu, v.y, d));
}
__device__ __forceinline__ float gelu_half(float v) {
    float z = v * fmaf(v * v, 8.0f * 0.7978845608f * 0.044715f, 2.0f * 0.7978845608f);
    float t;
    asm("tanh.approx.f32 %0, %1;" : "=f"(t) : "f"(z));
    return fmaf(v, t, v);
}
__device__ __forceinline__ void mma_stats(float (&d)[4], uint32_t a, uint32_t b) {
    asm volatile("mma.sync.aligned.m16n8k16.row.col.f32.bf16.bf16.f32 {%0, %1, %2, %3}, {%4, %6, %5, %6}, {%4, %5}, {%0, %1, %2, %3};"
                 : "+f"(d[0]), "+f"(d[1]), "+f"(d[2]), "+f"(d[3]) : "r"(a), "r"(b), "r"(0x3f803f80u));
}

template <int TA, int TB>
__device__ __forceinline__ void wgmma_n128(float (&d)[64], uint64_t da, uint64_t db, uint32_t acc) {
    asm volatile(
        "{\n.reg .pred p;\nsetp.ne.b32 p, %68, 0;\n"
        "wgmma.mma_async.sync.aligned.m64n128k16.f32.bf16.bf16 "
        "{%0, %1, %2, %3, %4, %5, %6, %7, %8, %9, %10, %11, %12, %13, %14, %15, %16, %17, %18, %19, %20, %21, %22, %23, %24, %25, %26, %27, %28, %29, %30, %31, %32, %33, %34, %35, %36, %37, %38, %39, %40, %41, %42, %43, %44, %45, %46, %47, %48, %49, %50, %51, %52, %53, %54, %55, %56, %57, %58, %59, %60, %61, %62, %63}, "
        "%64, %65, p, 1, 1, %66, %67;\n}\n"
        :
        "+f"(d[0]), "+f"(d[1]), "+f"(d[2]), "+f"(d[3]), "+f"(d[4]), "+f"(d[5]), "+f"(d[6]), "+f"(d[7]),
        "+f"(d[8]), "+f"(d[9]), "+f"(d[10]), "+f"(d[11]), "+f"(d[12]), "+f"(d[13]), "+f"(d[14]), "+f"(d[15]),
        "+f"(d[16]), "+f"(d[17]), "+f"(d[18]), "+f"(d[19]), "+f"(d[20]), "+f"(d[21]), "+f"(d[22]), "+f"(d[23]),
        "+f"(d[24]), "+f"(d[25]), "+f"(d[26]), "+f"(d[27]), "+f"(d[28]), "+f"(d[29]), "+f"(d[30]), "+f"(d[31]),
        "+f"(d[32]), "+f"(d[33]), "+f"(d[34]), "+f"(d[35]), "+f"(d[36]), "+f"(d[37]), "+f"(d[38]), "+f"(d[39]),
        "+f"(d[40]), "+f"(d[41]), "+f"(d[42]), "+f"(d[43]), "+f"(d[44]), "+f"(d[45]), "+f"(d[46]), "+f"(d[47]),
        "+f"(d[48]), "+f"(d[49]), "+f"(d[50]), "+f"(d[51]), "+f"(d[52]), "+f"(d[53]), "+f"(d[54]), "+f"(d[55]),
        "+f"(d[56]), "+f"(d[57]), "+f"(d[58]), "+f"(d[59]), "+f"(d[60]), "+f"(d[61]), "+f"(d[62]), "+f"(d[63])
        : "l"(da), "l"(db), "n"(TA), "n"(TB), "r"(acc));
}

template <int TA, int TB>
__device__ __forceinline__ void wgmma_n112(float (&d)[56], uint64_t da, uint64_t db, uint32_t acc) {
    asm volatile(
        "{\n.reg .pred p;\nsetp.ne.b32 p, %60, 0;\n"
        "wgmma.mma_async.sync.aligned.m64n112k16.f32.bf16.bf16 "
        "{%0, %1, %2, %3, %4, %5, %6, %7, %8, %9, %10, %11, %12, %13, %14, %15, %16, %17, %18, %19, %20, %21, %22, %23, %24, %25, %26, %27, %28, %29, %30, %31, %32, %33, %34, %35, %36, %37, %38, %39, %40, %41, %42, %43, %44, %45, %46, %47, %48, %49, %50, %51, %52, %53, %54, %55}, "
        "%56, %57, p, 1, 1, %58, %59;\n}\n"
        :
        "+f"(d[0]), "+f"(d[1]), "+f"(d[2]), "+f"(d[3]), "+f"(d[4]), "+f"(d[5]), "+f"(d[6]), "+f"(d[7]),
        "+f"(d[8]), "+f"(d[9]), "+f"(d[10]), "+f"(d[11]), "+f"(d[12]), "+f"(d[13]), "+f"(d[14]), "+f"(d[15]),
        "+f"(d[16]), "+f"(d[17]), "+f"(d[18]), "+f"(d[19]), "+f"(d[20]), "+f"(d[21]), "+f"(d[22]), "+f"(d[23]),
        "+f"(d[24]), "+f"(d[25]), "+f"(d[26]), "+f"(d[27]), "+f"(d[28]), "+f"(d[29]), "+f"(d[30]), "+f"(d[31]),
        "+f"(d[32]), "+f"(d[33]), "+f"(d[34]), "+f"(d[35]), "+f"(d[36]), "+f"(d[37]), "+f"(d[38]), "+f"(d[39]),
        "+f"(d[40]), "+f"(d[41]), "+f"(d[42]), "+f"(d[43]), "+f"(d[44]), "+f"(d[45]), "+f"(d[46]), "+f"(d[47]),
        "+f"(d[48]), "+f"(d[49]), "+f"(d[50]), "+f"(d[51]), "+f"(d[52]), "+f"(d[53]), "+f"(d[54]), "+f"(d[55])
        : "l"(da), "l"(db), "n"(TA), "n"(TB), "r"(acc));
}

template <int KIND, int NACC>
__device__ __forceinline__ void mma_run(float (&acc)[NACC], uint32_t sb, int n0, int n1, int relUse, uint32_t relAddr, uint32_t& spin) {
    constexpr uint32_t sa = KIND == 0 ? 128 : (KIND == 2 ? 16 : 2), sbb = KIND == 0 ? 16 : 128;
    constexpr uint32_t lboA = KIND == 0 ? 512 : (KIND == 2 ? 8 : 1), lboB = KIND == 0 ? 8 : 512;
    constexpr uint32_t hiA = 64u | (KIND == 2 ? 0u : 0x40000000u), hiB = 64u | (KIND == 0 ? 0u : 0x40000000u);
    const uint32_t base = ((sb & 0x3FFFF) >> 4) | (lboA << 16);
    uint32_t bar = sb + BAR_FULL + n0 * 8;
    const uint32_t barEnd = sb + BAR_FULL + n1 * 8;
    const uint32_t barRel = sb + BAR_FULL + (relUse + 1) * 8;
    uint32_t slot = ((n0 + 2) & 7) * (SLOT_BYTES / 16);
    uint64_t dA = ((uint64_t)hiA << 32) | (base + slot);
    uint64_t dB = ((uint64_t)hiB << 32) | (base + slot + (512u + ((lboB - lboA) << 16)));
    uint32_t keep = 0;
    mbar_wait0(bar, spin);
#pragma unroll 1
    while (true) {
        wg_fence();
#pragma unroll
        for (int kk = 0; kk < 4; kk++) {
            if constexpr (KIND == 0) wgmma_n112<1, 1>(acc, dA + kk * sa, dB + kk * sbb, 1);
            if constexpr (KIND == 1) wgmma_n128<0, 1>(acc, dA + kk * sa, dB + kk * sbb, kk ? 1u : keep);
            if constexpr (KIND == 2) wgmma_n128<1, 1>(acc, dA + kk * sa, dB + kk * sbb, 1);
        }
        wg_commit();
        keep = 1;
        const bool rel = bar == barRel;
        bar += 8;
        const bool ok = mbar_test(bar);
        slot = slot == (NSLOT - 1) * (SLOT_BYTES / 16) ? 0u : slot + SLOT_BYTES / 16;
        dA = ((uint64_t)hiA << 32) | (base + slot);
        dB = ((uint64_t)hiB << 32) | (base + slot + (512u + ((lboB - lboA) << 16)));
        wg_wait<1>();
        if (rel) mbar_arrive_cluster(relAddr);
        if (bar == barEnd) break;
        if (!ok) mbar_wait0(bar, spin);
    }
}

__device__ __forceinline__ void poll_round(const unsigned* cnt, unsigned target, int pend, uint32_t bar, const char* pf, uint32_t& spin) {
    int pfn = pf ? 0 : 16;
#pragma unroll 1
    while (true) {
        unsigned v = target - 1u;
        if (pend > 0) v = ld_poll(cnt);
        if (pfn < 16) {
            l2_prefetch_line(pf + pfn * (NCTA * 4096));
            l2_prefetch_line(pf + (pfn + 1) * (NCTA * 4096));
            pfn += 2;
        }
        if ((int)(v - target) >= 0) {
            fence_async_global();
            mbar_arrive_n(bar, pend);
            pend = 0;
        }
        if (pfn >= 16 && __all_sync(0xffffffffu, pend == 0)) break;
        if (++spin > SPIN_LIMIT) __trap();
    }
}
__device__ __forceinline__ void bulk_run(uint32_t sb, int n0, int n1, int step, const char* src, int srcStep, int wrapAt, int wrapBy,
                                         uint32_t dstOff, uint32_t bytes, uint16_t mask, uint32_t& spin PROF_PARM) {
#pragma unroll 1
    for (int n = n0; n < n1; n += step) {
        const char* s = src + (n >= wrapAt ? wrapBy : 0);
        const uint32_t dst = sb + dstOff + ((n + 2) & 7) * SLOT_BYTES;
        mbar_wait0(sb + BAR_EMPTY + n * 8, spin);
        bulk_mc(dst, s, bytes, sb + BAR_FULL + n * 8, mask);
        PROF_E(3, n);
        src += srcStep;
    }
}

__device__ __forceinline__ float4 state_params(float lr, float li, float ldt) {
    float dt = __bfloat162float(__float2bfloat16(expf(ldt)));
    float e = expf(dt * lr), sn, cs;
    sincosf(dt * li, &sn, &cs);
    float nr = e * cs - 1.0f, ni = e * sn;
    float inv = __fdividef(2.0f, lr * lr + li * li);
    return make_float4(e * cs, ni, (nr * lr + ni * li) * inv, (ni * lr - nr * li) * inv);
}

__global__ void __cluster_dims__(16, 1, 1) __launch_bounds__(384, 1)
fused_kernel(const Params p, const __grid_constant__ CUtensorMap mX, const __grid_constant__ CUtensorMap mBre,
             const __grid_constant__ CUtensorMap mBim, const __grid_constant__ CUtensorMap mW1,
             const __grid_constant__ CUtensorMap mCre, const __grid_constant__ CUtensorMap mCim,
             const __grid_constant__ CUtensorMap mW2, const __grid_constant__ CUtensorMap mHn,
             const __grid_constant__ CUtensorMap mOut) {
    extern __shared__ __align__(1024) unsigned char smem[];
    const long long t_start = clock64();
    const int tid = threadIdx.x;
    const int cta = blockIdx.x;
    const int tb = cta / 7, sl = cta - tb * 7;
    const char* bRows = (const char*)(tb < 8 ? p.bre : p.bim) + (sl * 64 + (tb & 7) * 8) * 896;
    {
        const int g4 = tid >> 6, ln = tid & 63;
        if (ln < 56 && g4 < 4 && (g4 == 3 || sl + 7 * g4 < 16))
            l2_prefetch_line((g4 == 3 ? bRows : (const char*)p.x + (tb * 128 + (sl + 7 * g4) * 8) * 896) + ln * 128);
        if (tid == 256) {
            asm volatile("prefetch.tensormap [%0];" ::"l"(&mX) : "memory");
            asm volatile("prefetch.tensormap [%0];" ::"l"(&mBre) : "memory");
            asm volatile("prefetch.tensormap [%0];" ::"l"(&mBim) : "memory");
            asm volatile("prefetch.tensormap [%0];" ::"l"(&mHn) : "memory");
            asm volatile("prefetch.tensormap [%0];" ::"l"(&mW1) : "memory");
        }
    }
    const int lane = tid & 31;
    const int warp = __shfl_sync(0xffffffffu, tid >> 5, 0);
    const uint32_t sb = __shfl_sync(0xffffffffu, smem_u32(smem), 0);
    if (warp == 9) {
        if (elect_one()) mbar_init(sb + BAR_RDY, 16);
        init_barriers<7>(sb + BAR_BU, 1);
    }
    cluster_arrive();
    if (warp < 4) init_barriers<40>(sb + BAR_FULL + warp * 320, warp < 2 ? 1 : 16);
    const int i8 = lane >> 2, c4 = lane & 3;
    uint32_t spin = 0;

    const int rank = cta & (CS - 1), cl = cta >> 4;
    const int fi = rank >> 2, di = rank & 3;
    const int fb = cl * 4 + fi;
    const int rlo = max(tb * 7 - cl * CS, 0), rhi = min(tb * 7 + 6 - cl * CS, CS - 1);
    const int rowSize = rhi - rlo + 1, rowPos = rank - rlo;
    const int colPos = rank / 7, cm = rank - colPos * 7;
    const int colSize = cm < 2 ? 3 : 2;
    const int rowStep = rowSize >= 4 ? 4 : (rowSize >= 2 ? 2 : 1);
    const uint16_t rowMask = (uint16_t)(((1u << rowSize) - 1u) << rlo);
    const uint16_t colMask = (uint16_t)((0x4081u << cm) & 0xffffu);
    auto issuer = [&](int n, int role) -> int {
        if (n < N_G1) return role ? (n & 3) * 4 + di : fi * 4 + (n & 3);
        return role ? rlo + (n & (rowStep - 1)) : cm + 7 * (n & 1);
    };
    unsigned epw = 0;

    if (warp >= (LN_WARM ? 3 : 4) && warp != 8 && warp != 9) {
        const int u = warp < 8 ? (warp - 4) & 7 : warp - 6;
        const int g = sl + 7 * (u >> 1);
        const bool live = opaque(g < 16);
        const int row = (u & 1) * 4 + (i8 & 3);
        const char* src = (const char*)p.x + (tb * 128 + g * 8 + row) * 896 + (i8 >> 2) * 448 + c4 * 16;
        uint4 v[7];
#pragma unroll
        for (int i = 0; i < 7; i++) {
            v[i] = make_uint4(0u, 0u, 0u, 0u);
            if (live) v[i] = __ldg((const uint4*)(src + i * 64));
        }
        if (warp > 3) epw = ld_relaxed(p.s->epoch) + 1u;
        float plr = 1.f, pli = 0.f, pdt = 0.f;
        if (u < 2) {
            const int st = sl * 64 + u * 32 + lane;
            plr = ldbf(p.lre + st); pli = ldbf(p.lim + st); pdt = ldbf(p.ldt + st);
        }
        float d0[4] = {0.f, 0.f, 0.f, 0.f}, d1[4] = {0.f, 0.f, 0.f, 0.f};
#pragma unroll
        for (int i = 0; i < 7; i++) {
            mma_stats(d0, v[i].x, v[i].y);
            mma_stats(d1, v[i].z, v[i].w);
        }
        float sq = (i8 & 1) ? d0[1] + d1[1] : d0[0] + d1[0];
        float sum = (i8 & 1) ? d0[3] + d1[3] : d0[2] + d1[2];
        sq = __shfl_sync(0xffffffffu, sq, (lane & 28) + (i8 >> 1));
        sum = __shfl_sync(0xffffffffu, sum, (lane & 28) + (i8 >> 1));
        sq += __shfl_xor_sync(0xffffffffu, sq, 16);
        sum += __shfl_xor_sync(0xffffffffu, sum, 16);
        if (GATE == 1 && warp >= 4 && sum != -1.2345e30f) asm volatile("bar.arrive 7, 352;" ::: "memory");
        {
            const float mean = sum * (1.0f / D_);
            const float var = fmaxf(fmaf(-mean, mean, sq * (1.0f / D_)), 0.f);
            const float r1 = rsqrtf(var + 1e-5f);
            const float r12 = 0.5f * r1 * rsqrtf(var * r1 * r1 + 1e-5f);
            const float off = -mean * r12;
            const uint32_t stg = sb + STAGE_OFF + min(u, 6) * 3584;
            const uint32_t sto = stg + ((i8 >> 2) * 28 + c4) * 64;
#pragma unroll
            for (int i = 0; i < 7; i++) {
                const uint32_t o0 = pack_bf16(fmaf(bf_lo(v[i].x), r12, off), fmaf(bf_hi(v[i].x), r12, off));
                const uint32_t o1 = pack_bf16(fmaf(bf_lo(v[i].y), r12, off), fmaf(bf_hi(v[i].y), r12, off));
                const uint32_t o2 = pack_bf16(fmaf(bf_lo(v[i].z), r12, off), fmaf(bf_hi(v[i].z), r12, off));
                const uint32_t o3 = pack_bf16(fmaf(bf_lo(v[i].w), r12, off), fmaf(bf_hi(v[i].w), r12, off));
                const uint32_t ad = sto + i * 256;
                asm volatile("st.shared.v4.u32 [%0], {%1, %2, %3, %4};" ::"r"(ad + (((i8 & 3) ^ ((ad >> 7) & 3)) * 16)),
                             "r"(o0), "r"(o1), "r"(o2), "r"(o3) : "memory");
            }
            fence_async_smem();
            __syncwarp();
            if (GATE == 2 && warp >= 4) asm volatile("bar.arrive 7, 352;" ::: "memory");
            if (live) {
                const bool lead = elect_one();
                if (lead) {
                    const int gg = tb * 16 + g;
                    tma2d_store(&mHn, (gg & 7) * 64 + (u & 1) * 32, (gg >> 3) * 56, stg);
                    bulk_commit();
                }
                if (c4 == 0 && lane < 16) st_ll(&p.s->stat[tb * 128 + g * 8 + row], r1, mean * r1, epw);
                if (lead) {
                    bulk_wait_all();
                    cnt_add_relaxed(&p.s->cnt[(CNT_LN + tb) * 32]);
                }
            }
            __syncwarp();
            if (u == 0 && lane == 0) PROF_T(10);
            if (warp >= 4) asm volatile("bar.arrive 2, 320;" ::: "memory");
            if (u < 2) {
                *(float4*)(smem + PARAM_OFF + (u * 32 + lane) * 16) = state_params(plr, pli, pdt);
                asm volatile("bar.arrive 6, 256;" ::: "memory");
                if (tid == 128) PROF_T(24);
            }
        }
    }

    if (warp == 8) {
        cluster_wait();
        nb_arrive(1, 160);
        if (elect_one()) {
            PROF_T(25);
            long long t = clock64();
#pragma unroll 1
            for (int k = 0; k < 6; k++) {
                if (rowPos == 0) tma5d_mc(sb + k * 32768 + 16384, &mX, k * 64, tb * 2, sb + BAR_BU + k * 8, rowMask);
                if (colPos == 0) tma2d_mc(sb + k * 32768, &mBre, k * 64, sl * 64, sb + BAR_BU + k * 8, colMask);
                if (colPos == 1) tma2d_mc(sb + k * 32768 + 8192, &mBim, k * 64, sl * 64, sb + BAR_BU + k * 8, colMask);
                t += BU_PACE;
                spin_until(t);
            }
        }
        __syncwarp();
        if (elect_one()) {
            mbar_wait0(sb + BAR_RDY, spin);
            if (rowPos == 0 || colPos < 2) {
                mbar_arrive_n(sb + BAR_K6, 16 - (rowPos == 0 ? rowSize : 0) - (colPos < 2 ? colSize : 0));
                mbar_wait0(sb + BAR_K6, spin);
                if (rowPos == 0) tma5d_mc(sb + 16384, &mX, 6 * 64, tb * 2, sb + BAR_BU + 48, rowMask);
                if (colPos == 0) tma2d_mc(sb, &mBre, 6 * 64, sl * 64, sb + BAR_BU + 48, colMask);
                if (colPos == 1) tma2d_mc(sb + 8192, &mBim, 6 * 64, sl * 64, sb + BAR_BU + 48, colMask);
            }
            PROF_T(28);
            const uint16_t maskW1 = (uint16_t)(0xFu << (fi * 4));
#pragma unroll 1
            for (int n = di; n < N_G1; n += 4) {
                mbar_wait0(sb + BAR_EMPTY + n * 8, spin);
                PROF_E(0, n);
                tma2d_mc(sb + ((n + 2) & 7) * SLOT_BYTES, &mW1, fb * 64, n * 64, sb + BAR_FULL + n * 8, maskW1);
            }
#pragma unroll 1
            for (int k = colPos < 2 ? colPos : N_CP; k < N_CP; k += 2) {
                const int n = k + N_G1;
                mbar_wait0(sb + BAR_EMPTY + n * 8, spin);
                PROF_E(0, n);
                tma2d_mc(sb + ((n + 2) & 7) * SLOT_BYTES, k >= 7 ? &mCim : &mCre, (k >= 7 ? k - 7 : k) * 64, sl * 64, sb + BAR_FULL + n * 8, colMask);
            }
#pragma unroll 1
            for (int k = rowPos < rowStep ? N_CP + ((rowPos - N_CP) & (rowStep - 1)) : N_ALL; k < N_CP + N_G2; k += rowStep) {
                const int n = k + N_G1;
                mbar_wait0(sb + BAR_EMPTY + n * 8, spin);
                PROF_E(0, n);
                const int kf = k - N_CP + cl * 4;
                tma3d_mc(sb + ((n + 2) & 7) * SLOT_BYTES + 8192, &mW2, 0, (kf >= N_G2 ? kf - N_G2 : kf) * 64, tb * 2, sb + BAR_FULL + n * 8, rowMask);
            }
        }
    } else if (warp == 9) {
        if (lane < 7) mbar_expect_tx(sb + BAR_BU + lane * 8, 32768);
        const unsigned ep = ld_relaxed(p.s->epoch) + 1u;
        {
            uint4 v[14];
#pragma unroll
            for (int i = 0; i < 14; i++) v[i] = __ldg((const uint4*)(bRows + i8 * 896 + c4 * 16 + i * 64));
            const char* pf = (const char*)p.w1 + cta * 4096 + lane * 128;
            spin_until(t_start + PF_START);
#pragma unroll 1
            for (int j = 0; j < PF_FIRST; j++) l2_prefetch_line(pf + j * (NCTA * 4096));
            float d0[4] = {0.f, 0.f, 0.f, 0.f}, d1[4] = {0.f, 0.f, 0.f, 0.f};
#pragma unroll
            for (int i = 0; i < 14; i++) {
                mma_stats(d0, v[i].x, v[i].y);
                mma_stats(d1, v[i].z, v[i].w);
            }
            if (lane < 4) st_ll((uint4*)&p.s->bsum[sl * 128 + tb * 8 + lane * 2], d0[2] + d1[2], d0[3] + d1[3], ep);
            __syncwarp();
            if (GATE) nb_arrive(7, GATE == 3 ? 160 : 352);
#pragma unroll 1
            for (int j = PF_FIRST; j < 16; j++) {
                l2_prefetch_line(pf + j * (NCTA * 4096));
                __nanosleep(PF1_NS);
            }
            cluster_wait();
        }
        if (elect_one()) {
            mbar_wait0(sb + BAR_RDY, spin);
            bulk_run(sb, fi, N_G1, 4, (const char*)p.s->hn + di * 14336 + fi * 57344, 4 * 57344, 1 << 30, 0, 8192, 14336,
                     (uint16_t)(0x1111u << di), spin PROF_ARG);
            if (rowPos < rowStep)
                bulk_run(sb, N_G1 + rowPos, N_G1 + N_CP, rowStep, (const char*)p.s->H + (tb * 14 + rowPos * 2) * 16384, rowStep * 32768,
                         N_G1 + 7, -13 * 16384, 8192, 16384, rowMask, spin PROF_ARG);
            if (colPos < 2)
                bulk_run(sb, N_G1 + N_CP + colPos, N_ALL, 2, (const char*)p.s->U + sl * 8192 + (colPos + cl * 4) * 57344, 2 * 57344,
                         N_ALL - cl * 4, -N_G2 * 57344, 0, 8192, colMask, spin PROF_ARG);
        }
    } else if (warp < 4) {
        const int w = warp;
        float2 lam[2], cf[2];
        const int st0 = sl * 64 + w * 16 + i8;
        const uint32_t buAddr = tid < 16 ? mapa(sb + BAR_EMPTY + (tid >> 1) * 8, issuer(tid >> 1, tid & 1))
                                         : mapa(sb + BAR_K6, tid == 16 ? rlo : (tid == 17 ? cm : cm + 7));
        const int buK = tid < 16 ? (0x66554322 >> ((tid >> 1) * 4)) & 7 : (tid < 19 ? 0 : -2);
        nb_sync(1, 160);
        if (warp == 3 && lane < CS) mbar_arrive_cluster(mapa(sb + BAR_RDY, lane));
        if (warp < 3) {
            const int n = tid;
            int pend = 0;
            if (n < N_ALL) {
                mbar_expect_tx(sb + BAR_FULL + n * 8, n < N_G1 ? 8192 + 14336 : SLOT_BYTES);
                const bool ia = issuer(n, 0) == rank, ib = issuer(n, 1) == rank;
                const int c = 16 - (ia ? (n < N_G1 ? 4 : colSize) : 0) - (ib ? (n < N_G1 ? 4 : rowSize) : 0);
                if (n < N_G1 + N_CP ? ib : ia) pend = c;
                else if (c < 16) mbar_arrive_n(sb + BAR_EMPTY + n * 8, c);
            }
            smem[PARAM_OFF + 1024 + n] = (unsigned char)pend;
            nb_arrive(15, 128);
        }
        if (tid == 0) PROF_T(29);
        {
            float aR[64], aI[64];
            uint64_t dk = mkdesc(sb, 16, 1024, 1);
            if (GATE) nb_sync(7, GATE == 3 ? 160 : 352);
#pragma unroll 1
            for (int k = 0; k < 7; k++) {
                mbar_wait0(sb + BAR_BU + k * 8, spin);
                if (k == 0 && tid == 0) PROF_T(0);
                wg_fence();
#pragma unroll
                for (int kk = 0; kk < 4; kk++) {
                    wgmma_n128<0, 0>(aR, dk + kk * 2, dk + 1024 + kk * 2, kk ? 1 : k);
                    wgmma_n128<0, 0>(aI, dk + 512 + kk * 2, dk + 1024 + kk * 2, kk ? 1 : k);
                }
                wg_commit();
                dk += k == 5 ? -5 * 2048 : 2048;
                if (k == 0) mbar_wait0(sb + BAR_RDY, spin);
                wg_wait<1>();
                if (buK == k - 1) mbar_arrive_cluster(buAddr);
            }
            wg_wait<0>();
            pin(aR);
            pin(aI);
            if (buK == 6) mbar_arrive_cluster(buAddr);
            if (tid == 0) PROF_T(1);
            asm volatile("bar.sync 6, 256;" ::: "memory");
            nb_sync(8, 160);
            const unsigned ep = *(const unsigned*)(smem + AUX_EPOCH);
            float2 bs[2], h[2][2];
#pragma unroll
            for (int hh = 0; hh < 2; hh++) {
                const float* bp = (const float*)(smem + AUX_BSUM) + w * 16 + i8 + hh * 8;
                bs[hh] = make_float2(-bp[0], -bp[64]);
                const float4 sp = *(const float4*)(smem + PARAM_OFF + (w * 16 + i8 + hh * 8) * 16);
                lam[hh] = make_float2(sp.x, sp.y);
                cf[hh] = make_float2(sp.z, sp.w);
                h[hh][0] = h[hh][1] = make_float2(0.f, 0.f);
            }
#pragma unroll
            for (int jj = 0; jj < (EXP & 1 ? 1 : 16); jj++) {
                const float4 st = *(const float4*)(smem + AUX_STAT + ((jj >> 3) * 4 + c4) * 144 + (jj & 7) * 16);
#pragma unroll
                for (int e = 0; e < 2; e++) {
                    const float r = e ? st.z : st.x, mr = e ? st.w : st.y;
#pragma unroll
                    for (int hh = 0; hh < 2; hh++) {
                        const int a = 4 * jj + 2 * hh + e;
                        aR[a] = fmaf(r, aR[a], mr * bs[hh].x);
                        aI[a] = fmaf(r, aI[a], mr * bs[hh].y);
                        h[hh][jj >> 3] = cfma(lam[hh], h[hh][jj >> 3], make_float2(aR[a], aI[a]));
                    }
                }
            }
            float2 lc[2], l64[2];
#pragma unroll
            for (int hh = 0; hh < 2; hh++) {
                float2 l16 = lam[hh];
#pragma unroll
                for (int z = 0; z < 4; z++) l16 = cmul(l16, l16);
                const float2 l32 = cmul(l16, l16);
                l64[hh] = cmul(l32, l32);
#pragma unroll
                for (int a = 0; a < 2; a++) {
                    float2 v = shfl_up2(h[hh][a], 1);
                    if (c4 >= 1) h[hh][a] = cfma(l16, v, h[hh][a]);
                    v = shfl_up2(h[hh][a], 2);
                    if (c4 >= 2) h[hh][a] = cfma(l32, v, h[hh][a]);
                }
                if (c4 == 3) {
                    const float2 f = cfma(l64[hh], h[hh][0], h[hh][1]);
                    st_ll(&p.s->fin[tb * D_ + st0 + hh * 8], f.x, f.y, ep);
                }
                float2 t = (c4 & 1) ? l16 : make_float2(1.f, 0.f);
                lc[hh] = (c4 & 2) ? cmul(t, l32) : t;
                const float2 f0 = make_float2(__shfl_sync(0xffffffffu, h[hh][0].x, lane | 3), __shfl_sync(0xffffffffu, h[hh][0].y, lane | 3));
#pragma unroll
                for (int a = 0; a < 2; a++) {
                    const float2 v = shfl_up2(h[hh][a], 1);
                    h[hh][a] = c4 >= 1 ? v : make_float2(0.f, 0.f);
                }
                h[hh][1] = cfma(lc[hh], f0, h[hh][1]);
            }
            nb_arrive(9, 192);
            if (tid == 0) PROF_T(2);
            pin(aR);
            pin(aI);
#pragma unroll
            for (int a = 0; a < (EXP & 1 ? 1 : 64); a++) {
                const float2 c = cf[(a >> 1) & 1];
                const float tr = fmaf(c.x, aR[a], -c.y * aI[a]);
                aI[a] = fmaf(-c.x, aI[a], -c.y * aR[a]);
                aR[a] = tr;
            }
            pin(aR);
            pin(aI);
            asm volatile("bar.sync 2, 320;" ::: "memory");
            nb_sync(10, 192);
            if (tid == 0) PROF_T(3);
#pragma unroll
            for (int hh = 0; hh < 2; hh++) {
                const float2 cy = cmul(lc[hh], *(const float2*)(smem + AUX_BSUM + (w * 16 + i8 + hh * 8) * 8));
                h[hh][0] = cmul(cf[hh], make_float2(h[hh][0].x + cy.x, h[hh][0].y + cy.y));
                h[hh][1] = cmul(cf[hh], cfma(l64[hh], cy, h[hh][1]));
                h[hh][0].y = -h[hh][0].y;
                h[hh][1].y = -h[hh][1].y;
                lam[hh].y = -lam[hh].y;
            }
#pragma unroll
            for (int q4 = 0; q4 < (EXP & 2 ? 0 : 4); q4++) {
#pragma unroll
                for (int hh = 0; hh < 2; hh++) {
                    uint32_t oR[4], oI[4];
                    float2& hc = h[hh][q4 >> 1];
#pragma unroll
                    for (int z = 0; z < 4; z++) {
                        const int a = 4 * (q4 * 4 + z) + 2 * hh;
                        const float2 h0 = cfma(lam[hh], hc, make_float2(aR[a], aI[a]));
                        hc = cfma(lam[hh], h0, make_float2(aR[a + 1], aI[a + 1]));
                        oR[z] = pack_bf16(h0.x, hc.x);
                        oI[z] = pack_bf16(h0.y, hc.y);
                    }
                    const int off = STAGE_OFF + (q4 >> 1) * 8192 + (w * 16 + hh * 8 + i8) * 128 + (((c4 * 2 + (q4 & 1)) ^ i8) * 16);
                    *(uint4*)(smem + off) = make_uint4(oR[0], oR[1], oR[2], oR[3]);
                    *(uint4*)(smem + off + 16384) = make_uint4(oI[0], oI[1], oI[2], oI[3]);
                }
            }
            fence_async_smem();
            nb_arrive(11, 160);
            if (tid == 0) PROF_T(4);
        }
        float acc[64];
        const int relUse = tid < 68 ? (tid >> 1) + N_G1 : 0;
        const uint32_t relAddr = mapa(sb + BAR_EMPTY + (relUse + NSLOT) * 8, issuer(relUse + NSLOT, tid & 1));
        cluster_wait();
        nb_sync(14, 256);
        if (tid == 0) PROF_T(7);
        mma_run<1>(acc, sb, N_G1, N_G1 + N_CP, relUse, relAddr, spin);
        if (tid == 0) PROF_T(19);
        mma_run<2>(acc, sb, N_G1 + N_CP, N_ALL, relUse, relAddr, spin);
        {
            const int dl = (w & 1) * 16 + i8;
            unsigned char* base = smem + STAGE_OFF + (w >> 1) * 16384 + (dl & 3) * 4;
            nb_sync(13, 256);
            wg_wait<0>();
            pin(acc);
            if (tid == 0) PROF_T(9);
#pragma unroll
            for (int half = 0; half < 2; half++) {
#pragma unroll
                for (int jj = half * 8; jj < half * 8 + 8; jj++) {
#pragma unroll
                    for (int e = 0; e < 2; e++) {
                        const int s7 = c4 * 2 + e;
                        const unsigned char* row = base + (jj * 8 + s7) * 128;
                        acc[4 * jj + e] += *(const float*)(row + (((dl >> 2) ^ s7) * 16));
                        acc[4 * jj + 2 + e] += *(const float*)(row + ((((dl >> 2) + 2) ^ s7) * 16));
                    }
                }
#pragma unroll
                for (int jj = half * 8; jj < half * 8 + 8; jj++) {
#pragma unroll
                    for (int e = 0; e < 2; e++) {
                        const int s7 = c4 * 2 + e;
                        unsigned char* row = base + (jj * 8 + s7) * 128;
                        *(float*)(row + (((dl >> 2) ^ s7) * 16)) = acc[4 * jj + e];
                        *(float*)(row + ((((dl >> 2) + 2) ^ s7) * 16)) = acc[4 * jj + 2 + e];
                    }
                }
                fence_async_smem();
                asm volatile("bar.sync %0, 64;" ::"r"(4 + (w >> 1)) : "memory");
                if ((tid & 63) == 0) {
                    tma2d_store(&mOut, sl * 64 + (w >> 1) * 32, tb * 128 + half * 64, sb + STAGE_OFF + (w >> 1) * 16384 + half * 8192);
                    bulk_commit();
                }
            }
            if (tid == 0 && cta == 0) p.s->epoch[0] = *(const unsigned*)(smem + AUX_EPOCH);
            if ((tid & 63) == 0) bulk_wait_read();
        }
    } else {
        const int w = warp - 4;
        if (w == 0 && lane == 0) PROF_T(18);
        float acc[56];
        {
            const float bias0 = 0.5f * ldbf(p.b1 + fb * 64 + (w & 3) * 16 + i8), bias1 = 0.5f * ldbf(p.b1 + fb * 64 + (w & 3) * 16 + i8 + 8);
#pragma unroll
            for (int j = 0; j < 14; j++) {
                acc[4 * j] = acc[4 * j + 1] = bias0;
                acc[4 * j + 2] = acc[4 * j + 3] = bias1;
            }
        }
        pin(acc);
        if (warp < 8) {
        cluster_wait();
        mbar_wait0(sb + BAR_RDY, spin);
        const int relUse = (tid - 128) >> 1;
        const uint32_t relAddr = mapa(sb + BAR_EMPTY + (relUse + NSLOT) * 8, issuer(relUse + NSLOT, tid & 1));
        mma_run<0>(acc, sb, 0, N_G1, relUse, relAddr, spin);
        nb_arrive(14, 256);
        nb_sync(12, 160);
        wg_wait<0>();
        pin(acc);
        if (relUse == N_G1 - 1) mbar_arrive_cluster(relAddr);
        if (w == 0 && lane == 0) PROF_T(12);
        } else {
            const int hh = warp - 10;
            const unsigned ep = epw;
            float2 l128;
            int pend[3];
            {
                if (warp == 11) {
                    nb_sync(15, 128);
#pragma unroll
                    for (int r = 0; r < 3; r++) pend[r] = smem[PARAM_OFF + 1024 + r * 32 + lane];
                    poll_round(&p.s->cnt[(CNT_LN + (lane >> 1)) * 32], ep * 32u, pend[0], sb + BAR_EMPTY + lane * 8,
                               nullptr, spin);
                    if (lane == 0) {
                        PROF_T(20);
                        asm volatile("prefetch.tensormap [%0];" ::"l"(&mCre) : "memory");
                        asm volatile("prefetch.tensormap [%0];" ::"l"(&mCim) : "memory");
                        asm volatile("prefetch.tensormap [%0];" ::"l"(&mW2) : "memory");
                        asm volatile("prefetch.tensormap [%0];" ::"l"(&mOut) : "memory");
                    }
                    if (lane < 28) {
                        l2_prefetch_line((const char*)p.cre + cta * 3584 + lane * 128);
                        l2_prefetch_line((const char*)p.cim + cta * 3584 + lane * 128);
                    }
                } else {
                    uint4 a[6];
                    int it = 0;
                    while (true) {
#pragma unroll
                        for (int c = 0; c < 4; c++) a[c] = ld_ll(&p.s->stat[tb * 128 + c * 32 + lane]);
                        a[4] = ld_ll(&p.s->bsum[sl * 128 + lane * 2]);
                        a[5] = ld_ll(&p.s->bsum[sl * 128 + 64 + lane * 2]);
                        bool ok = true;
#pragma unroll
                        for (int c = 0; c < 6; c++) ok = ok && a[c].y == ep && a[c].w == ep;
                        if (__all_sync(0xffffffffu, ok)) break;
                        if (++it > SPIN_LIMIT) __trap();
                    }
#pragma unroll
                    for (int c = 0; c < 4; c++) *(uint2*)(smem + AUX_STAT + (c * 2 + (lane >> 4)) * 144 + (lane & 15) * 8) = make_uint2(a[c].x, a[c].z);
                    *(uint2*)(smem + AUX_BSUM + lane * 8) = make_uint2(a[4].x, a[4].z);
                    *(uint2*)(smem + AUX_BSUM + 256 + lane * 8) = make_uint2(a[5].x, a[5].z);
                    if (lane == 0) *(unsigned*)(smem + AUX_EPOCH) = ep;
                    nb_arrive(8, 160);
                    if (lane == 0) PROF_T(23);
                }
                asm volatile("bar.sync 6, 256;" ::: "memory");
                l128 = *(const float2*)(smem + PARAM_OFF + (hh * 32 + lane) * 16);
#pragma unroll
                for (int z = 0; z < 7; z++) l128 = cmul(l128, l128);
            }
            {
                const uint4* fp = &p.s->fin[(tb - 15) * D_ + sl * 64 + hh * 32 + lane];
                uint4 f[15];
#pragma unroll
                for (int b = 0; b < 15; b++) f[b] = make_uint4(0u, 0u, 0u, 0u);
                nb_sync(9, 192);
                while (!(EXP & 32)) {
                    unsigned tags = 0;
#pragma unroll
                    for (int b = 0; b < 15; b++) {
                        if (b + tb >= 15) f[b] = ld_ll(fp + b * D_);
                    }
#pragma unroll
                    for (int b = 0; b < 15; b++) tags += f[b].y + f[b].w;
                    if (__all_sync(0xffffffffu, tags == 2u * tb * ep)) break;
                    if (++spin > SPIN_LIMIT) __trap();
                }
                float2 cy = make_float2(0.f, 0.f);
#pragma unroll
                for (int b = 0; b < 15; b++) cy = cfma(l128, cy, make_float2(__uint_as_float(f[b].x), __uint_as_float(f[b].z)));
                *(float2*)(smem + AUX_BSUM + hh * 256 + lane * 8) = cy;
                nb_arrive(10, 192);
            }
            if (warp == 11) {
#pragma unroll 1
                for (int r = 1; r < 3; r++) {
                    const int n = r * 32 + lane;
                    int kf = n - N_G1 - N_CP + cl * 4;
                    if (kf >= N_G2) kf -= N_G2;
                    const bool isH = n < N_G1 + N_CP;
                    poll_round(&p.s->cnt[(isH ? CNT_H + tb * 2 + (n >= N_G1 + 7) : CNT_U + min(kf, N_G2 - 1)) * 32], ep * (isH ? 7u : 4u),
                               r == 1 ? pend[1] : pend[2], sb + BAR_EMPTY + n * 8,
                               (r == 1 && !(EXP & 8)) ? (const char*)p.w2 + cta * 4096 + lane * 128 : nullptr, spin);
                    if (lane == 0 && r == 1) PROF_T(22);
                }
            } else {
                nb_sync(11, 160);
                if (elect_one()) {
                char* dst = (char*)p.s->H + (tb * 14 + sl * 2) * 16384;
#pragma unroll 1
                for (int j = 0; j < 32768; j += H_PIECE) {
                    if (!(EXP & 4)) bulk_store(dst + j, sb + STAGE_OFF + j, H_PIECE);
                    if (j == 16384 - H_PIECE) {
                        bulk_commit();
                        bulk_wait_all();
                        cnt_add_relaxed(&p.s->cnt[(CNT_H + tb * 2) * 32]);
                        PROF_T(30);
                    } else if (H_NS) __nanosleep(H_NS);
                }
                bulk_commit();
                bulk_wait_all();
                cnt_add_relaxed(&p.s->cnt[(CNT_H + tb * 2 + 1) * 32]);
                PROF_T(5);
                }
                __syncwarp();
                nb_arrive(12, 160);
            }
            cluster_wait();
        }
        if (warp < 8) {
        constexpr bool live = true;
        const uint32_t stU = sb + STAGE_OFF + (lane >> 4) * 1024 + (w * 2 + ((lane >> 3) & 1)) * 128 + (lane & 7) * 16;
        char* dstU = (char*)p.s->U + (fb * 56 + di * 14) * 1024;
#pragma unroll
        for (int j = 0; j < 14; j += 2) {
            uint32_t r0 = pack_bf16(gelu_half(acc[4 * j + 0]), gelu_half(acc[4 * j + 1]));
            uint32_t r1 = pack_bf16(gelu_half(acc[4 * j + 2]), gelu_half(acc[4 * j + 3]));
            uint32_t r2 = pack_bf16(gelu_half(acc[4 * j + 4]), gelu_half(acc[4 * j + 5]));
            uint32_t r3 = pack_bf16(gelu_half(acc[4 * j + 6]), gelu_half(acc[4 * j + 7]));
            if (live) asm volatile("stmatrix.sync.aligned.m8n8.x4.shared.b16 [%0], {%1, %2, %3, %4};" ::"r"(stU + j * 1024), "r"(r0), "r"(r1), "r"(r2), "r"(r3) : "memory");
            if (j == 6 && live) {
                fence_async_smem();
                wg_bar(3);
                if (tid == 128) { bulk_store(dstU, sb + STAGE_OFF, 8192); bulk_commit(); }
            }
        }
        if (live) {
        fence_async_smem();
        wg_bar(3);
        if (tid == 128) {
            PROF_T(13);
            bulk_store(dstU + 8192, sb + STAGE_OFF + 8192, 6144);
            bulk_commit();
            bulk_wait_all();
            cnt_add_relaxed(&p.s->cnt[(CNT_U + fb) * 32]);
            PROF_T(15);
        }
        {
            const int t = tid - 128, ch = t & 15, r0 = t >> 4;
            const uint2 dk = __ldg((const uint2*)(p.dsk + sl * 64 + ch * 4));
            const char* xp = (const char*)p.x + (tb * 128 + r0) * 896 + sl * 128 + ch * 8;
            const __nv_bfloat16* bp = p.b2 + tb * 128 + r0;
            float4* rs = (float4*)(smem + STAGE_OFF + (ch >> 3) * 16384 + r0 * 128 + (((ch & 7) ^ r0) * 16));
            wg_bar(3);
#pragma unroll 4
            for (int it = 0; it < 16; it++) {
                const uint2 xv = __ldg((const uint2*)(xp + it * (8 * 896)));
                const float b2v = ldbf(bp + it * 8);
                const float2 st = *(const float2*)(smem + AUX_STAT + (it >> 1) * 144 + ((it & 1) * 8 + r0) * 8);
                const float x0 = bf_lo(xv.x), x1 = bf_hi(xv.x), x2 = bf_lo(xv.y), x3 = bf_hi(xv.y);
                rs[it * 64] = make_float4(fmaf(fmaf(x0, st.x, -st.y), bf_lo(dk.x), x0 + b2v), fmaf(fmaf(x1, st.x, -st.y), bf_hi(dk.x), x1 + b2v),
                                           fmaf(fmaf(x2, st.x, -st.y), bf_lo(dk.y), x2 + b2v), fmaf(fmaf(x3, st.x, -st.y), bf_hi(dk.y), x3 + b2v));
            }
            nb_arrive(13, 256);
            if (tid == 128) PROF_T(6);
        }
        }
        }
    }
}

typedef CUresult (*EncodeFn)(CUtensorMap*, CUtensorMapDataType, cuuint32_t, void*, const cuuint64_t*, const cuuint64_t*,
                             const cuuint32_t*, const cuuint32_t*, CUtensorMapInterleave, CUtensorMapSwizzle,
                             CUtensorMapL2promotion, CUtensorMapFloatOOBfill);

bool encode(EncodeFn fn, CUtensorMap* m, CUtensorMapDataType dt, int rank, const void* ptr, const cuuint64_t* dims,
            const cuuint64_t* strides, const cuuint32_t* box, CUtensorMapSwizzle sw = CU_TENSOR_MAP_SWIZZLE_128B) {
    cuuint32_t es[5] = {1, 1, 1, 1, 1};
    return fn(m, dt, rank, (void*)ptr, dims, strides, box, es, CU_TENSOR_MAP_INTERLEAVE_NONE, sw,
              CU_TENSOR_MAP_L2_PROMOTION_L2_128B, CU_TENSOR_MAP_FLOAT_OOB_FILL_NONE) == CUDA_SUCCESS;
}

}

extern "C" void kernel_launch(void* const* d_in, const int* in_sizes, int n_in, void* d_out, int out_size) {
    (void)in_sizes; (void)n_in; (void)out_size;
    typedef const __nv_bfloat16* bp;
    Params p;
    p.x = (bp)d_in[0]; p.lre = (bp)d_in[1]; p.lim = (bp)d_in[2]; p.bre = (bp)d_in[3]; p.bim = (bp)d_in[4];
    p.cre = (bp)d_in[5]; p.cim = (bp)d_in[6]; p.ldt = (bp)d_in[7]; p.dsk = (bp)d_in[8];
    void* sp = nullptr;
    cudaGetSymbolAddress(&sp, g_s);
    p.s = (Scratch*)sp;
    p.out = (float*)d_out;
    p.w1 = (bp)d_in[10]; p.b1 = (bp)d_in[11]; p.w2 = (bp)d_in[12]; p.b2 = (bp)d_in[13];

    void* f = nullptr;
    cudaDriverEntryPointQueryResult qr;
    cudaGetDriverEntryPoint("cuTensorMapEncodeTiled", &f, cudaEnableDefault, &qr);
    EncodeFn fn = (EncodeFn)f;
    CUtensorMap mX, mBre, mBim, mW1, mCre, mCim, mW2, mHn, mOut;
    const CUtensorMapDataType BF = CU_TENSOR_MAP_DATA_TYPE_BFLOAT16;
    bool ok = true;
    {
        cuuint64_t d[5] = {448, 2, 4, 8, 32}, s[4] = {896, 16 * 896, 2 * 896, 64 * 896};
        cuuint32_t b[5] = {64, 2, 4, 8, 2};
        ok &= encode(fn, &mX, BF, 5, p.x, d, s, b);
    }
    {
        cuuint64_t d[2] = {448, 448}, s[1] = {896};
        cuuint32_t b[2] = {64, 64};
        ok &= encode(fn, &mBre, BF, 2, p.bre, d, s, b);
        ok &= encode(fn, &mBim, BF, 2, p.bim, d, s, b);
        ok &= encode(fn, &mCre, BF, 2, p.cre, d, s, b);
        ok &= encode(fn, &mCim, BF, 2, p.cim, d, s, b);
    }
    {
        cuuint64_t d[2] = {1792, 2048}, s[1] = {3584};
        cuuint32_t b[2] = {64, 64};
        ok &= encode(fn, &mW1, BF, 2, p.w1, d, s, b);
    }
    {
        cuuint64_t d[3] = {64, 1792, 32}, s[2] = {4096, 128};
        cuuint32_t b[3] = {64, 64, 2};
        ok &= encode(fn, &mW2, BF, 3, p.w2, d, s, b);
    }
    {
        cuuint64_t d[2] = {448, 2048}, s[1] = {1792};
        cuuint32_t b[2] = {32, 64};
        ok &= encode(fn, &mOut, CU_TENSOR_MAP_DATA_TYPE_FLOAT32, 2, d_out, d, s, b);
    }
    {
        cuuint64_t d[2] = {512, 1792}, s[1] = {1024};
        cuuint32_t b[2] = {32, 56};
        ok &= encode(fn, &mHn, BF, 2, p.s->hn, d, s, b, CU_TENSOR_MAP_SWIZZLE_64B);
    }
    cudaFuncSetAttribute(fused_kernel, cudaFuncAttributeMaxDynamicSharedMemorySize, SMEM_BYTES);
    cudaFuncSetAttribute(fused_kernel, cudaFuncAttributeNonPortableClusterSizeAllowed, 1);
    cudaLaunchConfig_t cfg = {};
    cfg.gridDim = dim3(NCTA);
    cfg.blockDim = dim3(384);
    cfg.dynamicSmemBytes = SMEM_BYTES;
    cfg.stream = cudaStreamPerThread;
    cudaLaunchAttribute at[1];
    at[0].id = cudaLaunchAttributeClusterDimension;
    at[0].val.clusterDim.x = CS;
    at[0].val.clusterDim.y = 1;
    at[0].val.clusterDim.z = 1;
    cfg.attrs = at;
    cfg.numAttrs = 1;
    cudaLaunchKernelEx(&cfg, fused_kernel, p, mX, mBre, mBim, mW1, mCre, mCim, mW2, mHn, mOut);
}
```

```cpp
#include <cuda_runtime.h>
#include <cuda.h>
#include <cuda_bf16.h>
#include <stdint.h>

namespace {

constexpr int S_ = 2048, D_ = 448, F_ = 1792;
constexpr int CS = 16, NCL = 7, NCTA = CS * NCL;
constexpr int NSLOT = 8;
constexpr int SLOT_BYTES = 24576;
constexpr int NSLOT1 = 9, SLOT1_BYTES = 22528;
constexpr int STAGE_OFF = NSLOT1 * SLOT1_BYTES;
constexpr int RCV_OFF = STAGE_OFF + 16384;
constexpr int RES_OFF = 212992;
constexpr int OUT_OFF = 2 * SLOT_BYTES;
constexpr int AUX_OFF = 229376;
constexpr int SMEM_BYTES = AUX_OFF + 3072;
constexpr int N_G1 = 32, N_CP = 14, N_G2 = 28, N_ALL = N_G1 + N_CP + N_G2;
constexpr int BAR_FULL = AUX_OFF;
constexpr int BAR_FN = AUX_OFF + 592;
constexpr int BAR_BS = AUX_OFF + 608;
constexpr int BAR_EMPTY = AUX_OFF + 640;
constexpr int BAR_BU = AUX_OFF + 1280;
constexpr int BAR_RDY = BAR_BU + 56;
constexpr int BAR_NIL = BAR_EMPTY + 592;
constexpr int BAR_K0 = BAR_EMPTY + 600;
constexpr int BAR_P1 = BAR_EMPTY + 608;
constexpr int BAR_CP = BAR_EMPTY + 616;
constexpr int BAR_K6 = BAR_EMPTY + 624;
constexpr int PARAM_OFF = RCV_OFF + 8192;
constexpr int AUX_STAT = AUX_OFF + 1344;
constexpr int AUX_BSUM = AUX_STAT + 1152;
constexpr int AUX_EPOCH = AUX_BSUM + 512;
constexpr int SPIN_LIMIT = 1 << 18;
#define BU_START 1800
#define BU_PACE 250
#define BU_N1 3
#define BU_GAP 900
#define BU_PACE2 430
#define B_LATE 500
#define PF_START 4000
#define STAT_START 4800
#define PREP_START 3000
#define H_CYC 100
#define H_GAP 1300
#define H_CYC2 200
#define LINK 2
#define PF_N0 10
#define PF_NS 40
#define W2_AHEAD 4
constexpr int PRE = 2, OUT_PARTS = 4;

constexpr int CNT_LN = 0, CNT_H = 32, CNT_U = 64, CNT_N = 92;

struct Scratch {
    unsigned cnt[CNT_N * 32];
    unsigned epoch[32 * 4];
    uint4 stat[S_];
    __nv_bfloat16 hn[S_ * D_];
    __nv_bfloat16 U[F_ * D_];
    __nv_bfloat16 H[S_ * 2 * D_];
};
__device__ __align__(1024) Scratch g_s;
#define PROF_T(k) do { } while (0)
#define PROF_PARM
#define PROF_ARG
#define PROF_E(r, n) do { } while (0)
#define PROF_N(r, n) do { } while (0)

struct Params {
    const __nv_bfloat16 *x, *bre, *bim;
    Scratch* s;
    const __nv_bfloat16 *lre, *lim, *ldt, *w1, *w2, *cre, *cim, *dsk, *b1, *b2;
    float* out;
    unsigned zero;
};

__device__ __forceinline__ uint32_t smem_u32(const void* p) { return (uint32_t)__cvta_generic_to_shared(p); }
__device__ __forceinline__ bool elect_one() {
    uint32_t p;
    asm volatile("{\n.reg .pred P;\nelect.sync _|P, 0xffffffff;\nselp.u32 %0, 1, 0, P;\n}" : "=r"(p));
    return p != 0;
}
__device__ __forceinline__ void mbar_init(uint32_t a, uint32_t cnt) {
    asm volatile("mbarrier.init.shared::cta.b64 [%0], %1;" ::"r"(a), "r"(cnt) : "memory");
}
__device__ __forceinline__ void mbar_expect_tx(uint32_t a, uint32_t bytes) {
    asm volatile("mbarrier.arrive.expect_tx.shared::cta.b64 _, [%0], %1;" ::"r"(a), "r"(bytes) : "memory");
}
__device__ __forceinline__ void mbar_arrive_n(uint32_t a, uint32_t n) {
    asm volatile("mbarrier.arrive.shared::cta.b64 _, [%0], %1;" ::"r"(a), "r"(n) : "memory");
}
template <int N>
__device__ __forceinline__ void init_barriers(uint32_t a, uint32_t cnt) {
    if (elect_one()) {
#pragma unroll
        for (int i = 0; i < N; i++) mbar_init(a + i * 8, cnt);
        asm volatile("fence.mbarrier_init.release.cluster;" ::: "memory");
    }
    __syncwarp();
}
__device__ __forceinline__ void mbar_arrive_cluster(uint32_t ra) {
    asm volatile("mbarrier.arrive.shared::cluster.b64 _, [%0];" ::"r"(ra) : "memory");
}
__device__ __forceinline__ uint32_t mapa(uint32_t a, uint32_t cta) {
    uint32_t r;
    asm volatile("mapa.shared::cluster.u32 %0, %1, %2;" : "=r"(r) : "r"(a), "r"(cta));
    return r;
}
__device__ __forceinline__ bool mbar_test(uint32_t a) {
    uint32_t ok;
    asm volatile("{\n.reg .pred p;\nmbarrier.test_wait.parity.shared::cta.b64 p, [%1], 0;\nselp.u32 %0, 1, 0, p;\n}"
                 : "=r"(ok) : "r"(a) : "memory");
    return ok != 0;
}
__device__ __forceinline__ void mbar_wait0(uint32_t a, uint32_t& spin) {
    asm volatile(
        "{\n.reg .pred p;\n"
        "WAIT_%=:\n"
        "mbarrier.try_wait.parity.shared::cta.b64 p, [%1], 0;\n"
        "@p bra DONE_%=;\n"
        "add.u32 %0, %0, 1;\n"
        "setp.lt.u32 p, %0, %2;\n"
        "@p bra WAIT_%=;\n"
        "trap;\n"
        "DONE_%=:\n}" : "+r"(spin) : "r"(a), "n"(SPIN_LIMIT) : "memory");
}
template <int N> __device__ __forceinline__ void pin2(float2 (&d)[N]) {
#pragma unroll
    for (int i = 0; i < N; i++) asm volatile("" : "+f"(d[i].x), "+f"(d[i].y)::"memory");
}
__device__ __forceinline__ void tma2d_mc(uint32_t dst, const CUtensorMap* m, int c0, int c1, uint32_t bar, uint16_t mask) {
    asm volatile(
        "cp.async.bulk.tensor.2d.shared::cluster.global.mbarrier::complete_tx::bytes.multicast::cluster"
        " [%0], [%1, {%3, %4}], [%2], %5;" ::"r"(dst), "l"(m), "r"(bar), "r"(c0), "r"(c1), "h"(mask) : "memory");
}
__device__ __forceinline__ void tma3d_mc(uint32_t dst, const CUtensorMap* m, int c0, int c1, int c2, uint32_t bar, uint16_t mask) {
    asm volatile(
        "cp.async.bulk.tensor.3d.shared::cluster.global.mbarrier::complete_tx::bytes.multicast::cluster"
        " [%0], [%1, {%3, %4, %5}], [%2], %6;" ::"r"(dst), "l"(m), "r"(bar), "r"(c0), "r"(c1), "r"(c2), "h"(mask) : "memory");
}
__device__ __forceinline__ uint32_t slot_off(int n) {
    return n < N_G1 ? (uint32_t)((n + 2) - 9 * (((n + 2) * 57) >> 9)) * SLOT1_BYTES : (uint32_t)((n + 7) & 7) * SLOT_BYTES;
}
__device__ __forceinline__ int g1k(int n, int cl) {
    const int k = n + cl * 4;
    return n >= 28 ? n : (k >= 28 ? k - 28 : k);
}
__device__ __forceinline__ void w2_prefetch(const CUtensorMap* m, int kf, int tb) {
    if (kf >= N_G2) kf -= N_G2;
    asm volatile("cp.async.bulk.prefetch.tensor.3d.L2.global [%0, {%1, %2, %3}];" ::"l"(m), "r"(0), "r"(kf * 64), "r"(tb * 2) : "memory");
}
__device__ __forceinline__ void tma5d(uint32_t dst, const CUtensorMap* m, int c0, int c4, uint32_t bar) {
    asm volatile(
        "cp.async.bulk.tensor.5d.shared::cluster.global.mbarrier::complete_tx::bytes"
        " [%0], [%1, {%3, %5, %5, %5, %4}], [%2];" ::"r"(dst), "l"(m), "r"(bar), "r"(c0), "r"(c4), "r"(0) : "memory");
}
__device__ __forceinline__ void st_async2(uint32_t dst, float a, float b, uint32_t bar) {
    asm volatile("st.async.shared::cluster.mbarrier::complete_tx::bytes.v2.f32 [%0], {%1, %2}, [%3];" ::"r"(dst), "f"(a), "f"(b), "r"(bar) : "memory");
}
__device__ __forceinline__ void bulk_mc(uint32_t dst, const void* src, uint32_t bytes, uint32_t bar, uint16_t mask) {
    asm volatile(
        "cp.async.bulk.shared::cluster.global.mbarrier::complete_tx::bytes.multicast::cluster"
        " [%0], [%1], %2, [%3], %4;" ::"r"(dst), "l"(src), "r"(bytes), "r"(bar), "h"(mask) : "memory");
}
__device__ __forceinline__ void bulk_store(void* dst, uint32_t src, uint32_t bytes) {
    asm volatile("cp.async.bulk.global.shared::cta.bulk_group [%0], [%1], %2;" ::"l"(dst), "r"(src), "r"(bytes) : "memory");
}
__device__ __forceinline__ void tma2d_store(const CUtensorMap* m, int c0, int c1, uint32_t src) {
    asm volatile("cp.async.bulk.tensor.2d.global.shared::cta.bulk_group [%0, {%2, %3}], [%1];" ::"l"(m), "r"(src), "r"(c0), "r"(c1) : "memory");
}
__device__ __forceinline__ void bulk_commit() { asm volatile("cp.async.bulk.commit_group;" ::: "memory"); }
__device__ __forceinline__ void bulk_wait_all() { asm volatile("cp.async.bulk.wait_group 0;" ::: "memory"); }
__device__ __forceinline__ void bulk_wait_read() { asm volatile("cp.async.bulk.wait_group.read 0;" ::: "memory"); }
__device__ __forceinline__ void fence_async_smem() { asm volatile("fence.proxy.async.shared::cta;" ::: "memory"); }
__device__ __forceinline__ void fence_async_global() { asm volatile("fence.proxy.async.global;" ::: "memory"); }
__device__ __forceinline__ void cluster_arrive() { asm volatile("barrier.cluster.arrive.relaxed.aligned;" ::: "memory"); }
__device__ __forceinline__ void cluster_wait() { asm volatile("barrier.cluster.wait.aligned;" ::: "memory"); }
__device__ __forceinline__ void wg_fence() { asm volatile("wgmma.fence.sync.aligned;" ::: "memory"); }
__device__ __forceinline__ void wg_commit() { asm volatile("wgmma.commit_group.sync.aligned;" ::: "memory"); }
template <int N> __device__ __forceinline__ void wg_wait() { asm volatile("wgmma.wait_group.sync.aligned %0;" ::"n"(N) : "memory"); }
template <int N> __device__ __forceinline__ void pin(float (&d)[N]) {
#pragma unroll
    for (int i = 0; i < N; i++) asm volatile("" : "+f"(d[i])::"memory");
}
__device__ __forceinline__ unsigned ld_relaxed(const unsigned* p) {
    unsigned v;
    asm volatile("ld.relaxed.gpu.global.u32 %0, [%1];" : "=r"(v) : "l"(p) : "memory");
    return v;
}
template <int PER_LANE>
__device__ __forceinline__ void readback(unsigned (&v)[PER_LANE], const char* base, int stride, int lines, int lane) {
    __syncwarp();
#pragma unroll
    for (int i = 0; i < PER_LANE; i++) v[i] = ld_relaxed((const unsigned*)(base + min(i * 32 + lane, lines - 1) * stride));
}
template <int PER_LANE>
__device__ __forceinline__ unsigned bump(const unsigned (&v)[PER_LANE], unsigned* c, unsigned zero) {
    unsigned acc = v[0];
#pragma unroll
    for (int i = 1; i < PER_LANE; i++) acc ^= v[i];
    const unsigned all = __reduce_or_sync(0xffffffffu, acc);
    if (elect_one()) asm volatile("red.relaxed.gpu.global.add.u32 [%0], %1;" ::"l"(c), "r"(1u + (all & zero)) : "memory");
    return all & zero;
}
__device__ __forceinline__ void st_ll(uint4* p, float a, float b, unsigned tag) {
    asm volatile("st.relaxed.gpu.global.v4.u32 [%0], {%1, %3, %2, %3};" ::"l"(p), "r"(__float_as_uint(a)), "r"(__float_as_uint(b)), "r"(tag) : "memory");
}
__device__ __forceinline__ uint4 ld_ll(const void* p) {
    uint4 v;
    asm volatile("ld.relaxed.gpu.global.v4.u32 {%0, %1, %2, %3}, [%4];" : "=r"(v.x), "=r"(v.y), "=r"(v.z), "=r"(v.w) : "l"(p) : "memory");
    return v;
}
__device__ __forceinline__ void l2_prefetch_line(const void* p) { asm volatile("prefetch.global.L2 [%0];" ::"l"(p) : "memory"); }
__device__ __forceinline__ uint32_t launder(uint32_t v, uint32_t zero) {
    asm volatile("xor.b32 %0, %0, %1;" : "+r"(v) : "r"(zero));
    return v;
}
__device__ __forceinline__ void sts32(uint32_t a, float v) {
    asm volatile("st.shared.f32 [%0], %1;" ::"r"(a), "f"(v) : "memory");
}
__device__ __forceinline__ float rsqrt_fast(float x) {
    float r;
    asm("rsqrt.approx.ftz.f32 %0, %1;" : "=f"(r) : "f"(x));
    return r;
}
__device__ __forceinline__ float4 lds128(uint32_t a) {
    float4 v;
    asm volatile("ld.shared.v4.f32 {%0, %1, %2, %3}, [%4];" : "=f"(v.x), "=f"(v.y), "=f"(v.z), "=f"(v.w) : "r"(a) : "memory");
    return v;
}
__device__ __forceinline__ uint32_t hfma2(uint32_t a, uint32_t b, uint32_t c) {
    uint32_t d;
    asm("fma.rn.bf16x2 %0, %1, %2, %3;" : "=r"(d) : "r"(a), "r"(b), "r"(c));
    return d;
}
__device__ __forceinline__ uint32_t hadd2(uint32_t a, uint32_t b) {
    uint32_t d;
    asm("add.rn.bf16x2 %0, %1, %2;" : "=r"(d) : "r"(a), "r"(b));
    return d;
}
__device__ __forceinline__ uint32_t hmul2(uint32_t a, uint32_t b) {
    uint32_t d;
    asm("mul.rn.bf16x2 %0, %1, %2;" : "=r"(d) : "r"(a), "r"(b));
    return d;
}
__device__ __forceinline__ void spin_until(long long t) { while (clock64() < t) { } }
__device__ __forceinline__ unsigned ld_acquire(const unsigned* p) {
    unsigned v;
    asm volatile("ld.acquire.gpu.global.u32 %0, [%1];" : "=r"(v) : "l"(p) : "memory");
    return v;
}
__device__ __forceinline__ void nb_arrive(int id, int n) { asm volatile("bar.arrive %0, %1;" ::"r"(id), "r"(n) : "memory"); }
__device__ __forceinline__ void nb_sync(int id, int n) { asm volatile("bar.sync %0, %1;" ::"r"(id), "r"(n) : "memory"); }
__device__ __forceinline__ uint64_t mkdesc(uint32_t addr, uint32_t lbo, uint32_t sbo, uint32_t swz) {
    return (uint64_t)((addr & 0x3FFFF) >> 4) | ((uint64_t)(lbo >> 4) << 16) | ((uint64_t)(sbo >> 4) << 32) | ((uint64_t)swz << 62);
}
__device__ __forceinline__ uint32_t pack_bf16(float lo, float hi) {
    uint32_t r;
    asm("cvt.rn.bf16x2.f32 %0, %1, %2;" : "=r"(r) : "f"(hi), "f"(lo));
    return r;
}
__device__ __forceinline__ float bf_lo(uint32_t v) { return __uint_as_float(v << 16); }
__device__ __forceinline__ float bf_hi(uint32_t v) { return __uint_as_float(v & 0xffff0000u); }
__device__ __forceinline__ float ldbf(const __nv_bfloat16* p) { return __bfloat162float(__ldg(p)); }
__device__ __forceinline__ float2 cmul(float2 a, float2 b) { return make_float2(a.x * b.x - a.y * b.y, a.x * b.y + a.y * b.x); }
__device__ __forceinline__ float2 cfma(float2 a, float2 b, float2 c) {
    return make_float2(fmaf(a.x, b.x, fmaf(-a.y, b.y, c.x)), fmaf(a.x, b.y, fmaf(a.y, b.x, c.y)));
}
__device__ __forceinline__ float gelu_half(float v) {
    float z = v * fmaf(v * v, 8.0f * 0.7978845608f * 0.044715f, 2.0f * 0.7978845608f);
    float t;
    asm("tanh.approx.f32 %0, %1;" : "=f"(t) : "f"(z));
    return fmaf(v, t, v);
}
__device__ __forceinline__ void mma_stats(float (&d)[4], uint32_t a, uint32_t b) {
    asm("mma.sync.aligned.m16n8k16.row.col.f32.bf16.bf16.f32 {%0, %1, %2, %3}, {%4, %6, %5, %6}, {%4, %5}, {%0, %1, %2, %3};"
                 : "+f"(d[0]), "+f"(d[1]), "+f"(d[2]), "+f"(d[3]) : "r"(a), "r"(b), "r"(0x3f803f80u));
}

template <int TA, int TB>
__device__ __forceinline__ void wgmma_n128(float (&d)[64], uint64_t da, uint64_t db, uint32_t acc) {
    asm volatile(
        "{\n.reg .pred p;\nsetp.ne.b32 p, %68, 0;\n"
        "wgmma.mma_async.sync.aligned.m64n128k16.f32.bf16.bf16 "
        "{%0, %1, %2, %3, %4, %5, %6, %7, %8, %9, %10, %11, %12, %13, %14, %15, %16, %17, %18, %19, %20, %21, %22, %23, %24, %25, %26, %27, %28, %29, %30, %31, %32, %33, %34, %35, %36, %37, %38, %39, %40, %41, %42, %43, %44, %45, %46, %47, %48, %49, %50, %51, %52, %53, %54, %55, %56, %57, %58, %59, %60, %61, %62, %63}, "
        "%64, %65, p, 1, 1, %66, %67;\n}\n"
        :
        "+f"(d[0]), "+f"(d[1]), "+f"(d[2]), "+f"(d[3]), "+f"(d[4]), "+f"(d[5]), "+f"(d[6]), "+f"(d[7]),
        "+f"(d[8]), "+f"(d[9]), "+f"(d[10]), "+f"(d[11]), "+f"(d[12]), "+f"(d[13]), "+f"(d[14]), "+f"(d[15]),
        "+f"(d[16]), "+f"(d[17]), "+f"(d[18]), "+f"(d[19]), "+f"(d[20]), "+f"(d[21]), "+f"(d[22]), "+f"(d[23]),
        "+f"(d[24]), "+f"(d[25]), "+f"(d[26]), "+f"(d[27]), "+f"(d[28]), "+f"(d[29]), "+f"(d[30]), "+f"(d[31]),
        "+f"(d[32]), "+f"(d[33]), "+f"(d[34]), "+f"(d[35]), "+f"(d[36]), "+f"(d[37]), "+f"(d[38]), "+f"(d[39]),
        "+f"(d[40]), "+f"(d[41]), "+f"(d[42]), "+f"(d[43]), "+f"(d[44]), "+f"(d[45]), "+f"(d[46]), "+f"(d[47]),
        "+f"(d[48]), "+f"(d[49]), "+f"(d[50]), "+f"(d[51]), "+f"(d[52]), "+f"(d[53]), "+f"(d[54]), "+f"(d[55]),
        "+f"(d[56]), "+f"(d[57]), "+f"(d[58]), "+f"(d[59]), "+f"(d[60]), "+f"(d[61]), "+f"(d[62]), "+f"(d[63])
        : "l"(da), "l"(db), "n"(TA), "n"(TB), "r"(acc));
}

template <int TA, int TB>
__device__ __forceinline__ void wgmma_n112(float (&d)[56], uint64_t da, uint64_t db, uint32_t acc) {
    asm volatile(
        "{\n.reg .pred p;\nsetp.ne.b32 p, %60, 0;\n"
        "wgmma.mma_async.sync.aligned.m64n112k16.f32.bf16.bf16 "
        "{%0, %1, %2, %3, %4, %5, %6, %7, %8, %9, %10, %11, %12, %13, %14, %15, %16, %17, %18, %19, %20, %21, %22, %23, %24, %25, %26, %27, %28, %29, %30, %31, %32, %33, %34, %35, %36, %37, %38, %39, %40, %41, %42, %43, %44, %45, %46, %47, %48, %49, %50, %51, %52, %53, %54, %55}, "
        "%56, %57, p, 1, 1, %58, %59;\n}\n"
        :
        "+f"(d[0]), "+f"(d[1]), "+f"(d[2]), "+f"(d[3]), "+f"(d[4]), "+f"(d[5]), "+f"(d[6]), "+f"(d[7]),
        "+f"(d[8]), "+f"(d[9]), "+f"(d[10]), "+f"(d[11]), "+f"(d[12]), "+f"(d[13]), "+f"(d[14]), "+f"(d[15]),
        "+f"(d[16]), "+f"(d[17]), "+f"(d[18]), "+f"(d[19]), "+f"(d[20]), "+f"(d[21]), "+f"(d[22]), "+f"(d[23]),
        "+f"(d[24]), "+f"(d[25]), "+f"(d[26]), "+f"(d[27]), "+f"(d[28]), "+f"(d[29]), "+f"(d[30]), "+f"(d[31]),
        "+f"(d[32]), "+f"(d[33]), "+f"(d[34]), "+f"(d[35]), "+f"(d[36]), "+f"(d[37]), "+f"(d[38]), "+f"(d[39]),
        "+f"(d[40]), "+f"(d[41]), "+f"(d[42]), "+f"(d[43]), "+f"(d[44]), "+f"(d[45]), "+f"(d[46]), "+f"(d[47]),
        "+f"(d[48]), "+f"(d[49]), "+f"(d[50]), "+f"(d[51]), "+f"(d[52]), "+f"(d[53]), "+f"(d[54]), "+f"(d[55])
        : "l"(da), "l"(db), "n"(TA), "n"(TB), "r"(acc));
}

__device__ __forceinline__ void mma_ones(float (&d)[4], uint32_t a, uint32_t b) {
    asm("mma.sync.aligned.m16n8k16.row.col.f32.bf16.bf16.f32 {%0, %1, %2, %3}, {%6, %6, %6, %6}, {%4, %5}, {%0, %1, %2, %3};"
        : "+f"(d[0]), "+f"(d[1]), "+f"(d[2]), "+f"(d[3]) : "r"(a), "r"(b), "r"(0x3f803f80u));
}

template <int KIND, int NACC>
__device__ __forceinline__ void mma_run(float (&acc)[NACC], uint32_t sb, int n0, int n1, int relUse, uint32_t relAddr, uint32_t& spin) {
    constexpr uint32_t sa = KIND == 0 ? 128 : (KIND == 2 ? 16 : 2), sbb = KIND == 0 ? 16 : 128;
    constexpr uint32_t lboA = KIND == 0 ? 512 : (KIND == 2 ? 8 : 1), lboB = KIND == 0 ? 8 : 512;
    constexpr uint32_t hiA = 64u | (KIND == 2 ? 0u : 0x40000000u), hiB = 64u | (KIND == 0 ? 0u : 0x40000000u);
    const uint32_t base = ((sb & 0x3FFFF) >> 4) | (lboA << 16);
    uint32_t bar = sb + BAR_FULL + n0 * 8;
    const uint32_t barEnd = sb + BAR_FULL + n1 * 8;
    const uint32_t barRel = sb + BAR_FULL + (relUse + 1) * 8;
    constexpr uint32_t pitch = (KIND == 0 ? SLOT1_BYTES : SLOT_BYTES) / 16;
    const uint32_t loEnd = base + (KIND == 0 ? NSLOT1 : NSLOT) * pitch;
    uint32_t lo = base + slot_off(n0) / 16;
    uint32_t keep = 0;
    auto mma = [&](uint32_t l, int kk, uint32_t k) {
        const uint64_t dA = (((uint64_t)hiA << 32) | l) + kk * sa;
        const uint64_t dB = (((uint64_t)hiB << 32) | (l + (512u + ((lboB - lboA) << 16)))) + kk * sbb;
        if constexpr (KIND == 0) wgmma_n112<1, 1>(acc, dA, dB, 1);
        if constexpr (KIND == 1) wgmma_n128<0, 1>(acc, dA, dB, k);
        if constexpr (KIND == 2) wgmma_n128<1, 1>(acc, dA, dB, 1);
    };
    mbar_wait0(bar, spin);
    if constexpr (KIND != 2) mbar_wait0(sb + (KIND == 0 ? BAR_P1 : BAR_CP), spin);
#pragma unroll 1
    while (true) {
        wg_fence();
        mma(lo, 0, keep);
        mma(lo, 1, 1);
        wg_commit();
        wg_wait<1>();
        if (bar == barRel) mbar_arrive_cluster(relAddr);
        uint32_t nlo, go;
        asm volatile(
            "{\n.reg .pred p, q;\n"
            "add.u32 %0, %0, 8;\n"
            "mbarrier.test_wait.parity.shared::cta.b64 p, [%0], 0;\n"
            "setp.ne.and.u32 p, %0, %4, p;\n"
            "selp.u32 %2, 1, 0, p;\n"
            "add.u32 %1, %3, %7;\n"
            "setp.eq.u32 q, %1, %5;\n"
            "selp.u32 %1, %6, %1, q;\n}"
            : "+r"(bar), "=&r"(nlo), "=r"(go) : "r"(lo), "r"(barEnd), "r"(loEnd), "r"(base), "n"(pitch) : "memory");
        mma(lo, 2, 1);
        mma(lo, 3, 1);
        wg_commit();
        keep = 1;
        lo = nlo;
        if (!go) {
            if (bar == barEnd) break;
            mbar_wait0(bar, spin);
        }
    }
}

__device__ __forceinline__ void poll_round(const unsigned* cnt, unsigned target, int pend, uint32_t bar, uint32_t& spin) {
#pragma unroll 1
    while (!__all_sync(0xffffffffu, pend == 0)) {
        if (pend > 0 && (int)(ld_acquire(cnt) - target) >= 0) {
            mbar_arrive_n(bar, pend);
            pend = 0;
        }
        if (++spin > SPIN_LIMIT) __trap();
    }
}
__device__ __forceinline__ void bulk_run(uint32_t sb, int n0, int n1, int step, const char* src, int srcStep, int wrapAt, int wrapBy,
                                         uint32_t dstOff, uint32_t bytes, uint16_t mask, uint32_t& spin PROF_PARM) {
#pragma unroll 1
    for (int n = n0; n < n1; n += step) {
        const char* s = src + (n >= wrapAt ? wrapBy : 0);
        const uint32_t dst = sb + dstOff + ((n + 7) & 7) * SLOT_BYTES;
        mbar_wait0(sb + BAR_EMPTY + n * 8, spin);
        bulk_mc(dst, s, bytes, sb + BAR_FULL + n * 8, mask);
        PROF_E(3, n);
        src += srcStep;
    }
}

__device__ __forceinline__ float4 state_params(float lr, float li, float ldt) {
    float dt = __bfloat162float(__float2bfloat16(expf(ldt)));
    float e = expf(dt * lr), sn, cs;
    {
        const float a = dt * li, k = rintf(a * 0.15915494309f);
        const float r = fmaf(k, 1.7484555e-7f, fmaf(k, -6.2831855f, a));
        sn = __sinf(r);
        cs = __cosf(r);
    }
    float nr = e * cs - 1.0f, ni = e * sn;
    float inv = __fdividef(2.0f, lr * lr + li * li);
    return make_float4(e * cs, ni, (nr * lr + ni * li) * inv, (ni * lr - nr * li) * inv);
}

__global__ void __cluster_dims__(16, 1, 1) __launch_bounds__(512, 1)
fused_kernel(const Params p, const __grid_constant__ CUtensorMap mX, const __grid_constant__ CUtensorMap mBre,
             const __grid_constant__ CUtensorMap mBim, const __grid_constant__ CUtensorMap mW1,
             const __grid_constant__ CUtensorMap mCre, const __grid_constant__ CUtensorMap mCim,
             const __grid_constant__ CUtensorMap mW2, const __grid_constant__ CUtensorMap mHn,
             const __grid_constant__ CUtensorMap mOut) {
    extern __shared__ __align__(1024) unsigned char smem[];
    const long long t_start = clock64();
    const int tid = threadIdx.x;
    const int cta = blockIdx.x;
    if (tid < 128) l2_prefetch_line((const char*)p.x + (cta * 128 + tid) * 128);
    const int tb = cta / 7, sl = cta - tb * 7;
    const int rank = cta & (CS - 1), cl = cta >> 4;
    if (tid == 256) {
        asm volatile("prefetch.tensormap [%0];" ::"l"(&mX) : "memory");
        asm volatile("prefetch.tensormap [%0];" ::"l"((rank & 1) ? &mBim : &mBre) : "memory");
        asm volatile("prefetch.tensormap [%0];" ::"l"(&mHn) : "memory");
    }
    const int lane = tid & 31;
    const int warp = __shfl_sync(0xffffffffu, tid >> 5, 0);
    const uint32_t sb = __shfl_sync(0xffffffffu, smem_u32(smem), 0);
    if (warp == 9) {
        if (elect_one()) mbar_init(sb + BAR_RDY, 16);
        init_barriers<7>(sb + BAR_BU, 1);
    }
    cluster_arrive();
    if (warp < 4) init_barriers<40>(sb + BAR_FULL + warp * 320, warp < 2 ? 1 : 32);
    const int i8 = lane >> 2, c4 = lane & 3;
    uint32_t spin = 0;

    const int fi = rank >> 2, di = rank & 3;
    const int fb = cl * 4 + fi;
    const int rlo = max(tb * 7 - cl * CS, 0), rhi = min(tb * 7 + 6 - cl * CS, CS - 1);
    const int rowSize = rhi - rlo + 1, rowPos = rank - rlo;
    const int colPos = rank / 7, cm = rank - colPos * 7;
    const int colSize = cm < 2 ? 3 : 2;
    const int rowStep = rowSize >= 4 ? 4 : (rowSize >= 2 ? 2 : 1);
    const uint16_t rowMask = (uint16_t)(((1u << rowSize) - 1u) << rlo);
    const uint16_t colMask = (uint16_t)((0x4081u << cm) & 0xffffu);
    auto issuer = [&](int n, int role) -> int {
        if (n < N_G1) return role ? (n & 3) * 4 + di : fi * 4 + (n & 3);
        return role ? rlo + (n & (rowStep - 1)) : cm + 7 * (n & 1);
    };
    float bias0 = 0.f, bias1 = 0.f;

    unsigned rb3[2] = {0u, 0u};
    if ((warp >= 4 && warp < 8) || ((warp >> 1) == 5 && sl < 2)) {
        const int u = warp < 8 ? warp - 4 : warp - 6;
        const int gg = u < 4 ? cta * 2 + (u >> 1) : 224 + tb * 2 + sl;
        const int row = (u & 1) * 4 + (i8 & 3);
        const char* src = (const char*)p.x + (gg * 8 + row) * 896 + (i8 >> 2) * 448 + c4 * 16;
        const unsigned epw = __ldcg(p.s->epoch) + 1u;
        uint4 v[7];
#pragma unroll
        for (int i = 0; i < 7; i++) v[i] = __ldg((const uint4*)(src + i * 64));
        const uint32_t stp = sb + NSLOT * SLOT_BYTES + (u < 4 ? (u >> 1) + 1 : 0) * 7168;
        const int ch0 = (i8 >> 2) * 28 + c4;
        const uint32_t sto0 = stp + ch0 * 128 + ((row ^ (ch0 & 7)) * 16), sto1 = sto0 ^ 64;
        float d0[4] = {0.f, 0.f, 0.f, 0.f}, d1[4] = {0.f, 0.f, 0.f, 0.f};
        float xf[56];
#pragma unroll
        for (int i = 0; i < 7; i++) {
            mma_stats(d0, v[i].x, v[i].y);
            mma_stats(d1, v[i].z, v[i].w);
            const uint32_t uu[4] = {v[i].x, v[i].y, v[i].z, v[i].w};
#pragma unroll
            for (int z = 0; z < 4; z++) {
                xf[i * 8 + 2 * z] = bf_lo(uu[z]);
                xf[i * 8 + 2 * z + 1] = bf_hi(uu[z]);
            }
        }
        float sq = (i8 & 1) ? d0[1] + d1[1] : d0[0] + d1[0];
        float sum = (i8 & 1) ? d0[3] + d1[3] : d0[2] + d1[2];
        {
            const int s0 = (lane & 12) + ((i8 & 3) >> 1);
            const float q0 = __shfl_sync(0xffffffffu, sq, s0), q1 = __shfl_sync(0xffffffffu, sq, s0 + 18);
            const float t0 = __shfl_sync(0xffffffffu, sum, s0), t1 = __shfl_sync(0xffffffffu, sum, s0 + 18);
            sq = q0 + q1;
            sum = t0 + t1;
        }
        if ((u >> 1) == 2) nb_arrive(7 + (__float_as_uint(sum) & p.zero), 480);
        const float mean = sum * (1.0f / D_);
        const float var = fmaxf(fmaf(-mean, mean, sq * (1.0f / D_)), 0.f);
        const float r1 = rsqrt_fast(var + 1e-5f);
        const float r12 = 0.5f * rsqrt_fast(fmaf(var + 1e-5f, 1e-5f, var));
        const float off = -mean * r12;
#pragma unroll
        for (int i = 0; i < 7; i++) {
            uint32_t o[4];
#pragma unroll
            for (int z = 0; z < 4; z++) o[z] = pack_bf16(fmaf(xf[i * 8 + 2 * z], r12, off), fmaf(xf[i * 8 + 2 * z + 1], r12, off));
            asm volatile("st.shared.v4.u32 [%0], {%1, %2, %3, %4};" ::"r"(((i & 1) ? sto1 : sto0) + i * 512),
                         "r"(o[0]), "r"(o[1]), "r"(o[2]), "r"(o[3]) : "memory");
        }
        fence_async_smem();
        if (u >= 4) {
            if (u == 5) nb_arrive(0, 64);
            if (c4 == 0 && lane < 16) st_ll(&p.s->stat[gg * 8 + row], r1, mean * r1, epw);
            if (u == 4) {
                nb_sync(0, 64);
                if (elect_one()) {
                    tma2d_store(&mHn, (gg & 7) * 64, (gg >> 3) * 56, stp);
                    bulk_commit();
                    bulk_wait_all();
                }
                readback(rb3, (const char*)p.s->hn + (gg >> 3) * 57344 + (gg & 7) * 128, 1024, 56, lane);
            }
        } else {
            nb_sync(4 + (u >> 1), 64);
            nb_arrive(7, 480);
            const bool lead = elect_one() && (u & 1);
            if (lead) {
                tma2d_store(&mHn, (gg & 7) * 64, (gg >> 3) * 56, stp);
                bulk_commit();
            }
            if (c4 == 0 && lane < 16) st_ll(&p.s->stat[gg * 8 + row], r1, mean * r1, epw);
            bias0 = ldbf(p.b1 + fb * 64 + u * 16 + i8);
            bias1 = ldbf(p.b1 + fb * 64 + u * 16 + i8 + 8);
            unsigned rb[2];
            if (u & 1) {
                if (lead) bulk_wait_all();
                __syncwarp();
                nb_arrive(2, 320);
                readback(rb, (const char*)p.s->hn + (gg >> 3) * 57344 + (gg & 7) * 128, 1024, 56, lane);
                const uint32_t own = mapa(sb + BAR_EMPTY + fi * 8, fi * 4 + (lane & 3));
                mbar_wait0(sb + BAR_RDY, spin);
                const unsigned z = bump(rb, &p.s->cnt[(CNT_LN + (gg >> 3)) * 32], p.zero);
                if (lane < 4) mbar_arrive_cluster(own + z);
                if (u == 1 && lane == 0) PROF_T(10);
            }
        }
    }

    if (warp == 8) {
        cluster_wait();
        nb_arrive(1, 160);
        if (elect_one()) {
            PROF_T(25);
            const CUtensorMap* mB = (rank & 1) ? &mBim : &mBre;
            uint32_t t = (uint32_t)t_start + BU_START;
#pragma unroll 1
            for (int k = 0; k < 7; k++) {
                while ((int)((uint32_t)clock64() - t) < 0) { }
                if (k == 6) {
                    mbar_wait0(sb + BAR_RDY, spin);
                    mbar_wait0(sb + BAR_K0, spin);
                    tma5d(sb + 16384, &mX, k * 64, rank * 2, sb + BAR_BU + k * 8);
                    mbar_wait0(sb + BAR_K6, spin);
                }
                const uint32_t dst = sb + (k < 6 ? k : 0) * 32768;
                tma2d_mc(dst + rank * 1024, mB, k * 64, cl * 64 + (rank >> 1) * 8, sb + BAR_BU + k * 8, 0xffff);
                if (k < 6) tma5d(dst + 16384, &mX, k * 64, rank * 2, sb + BAR_BU + k * 8);
                t += k + 1 == BU_N1 ? BU_GAP : (k < BU_N1 ? BU_PACE : BU_PACE2);
            }
            PROF_T(28);
            const uint16_t maskW1 = (uint16_t)(0xFu << (fi * 4));
#pragma unroll 1
            for (int n = di; n < N_G1; n += 4) {
                mbar_wait0(sb + BAR_EMPTY + n * 8, spin);
                PROF_E(0, n);
                tma2d_mc(sb + slot_off(n), &mW1, fb * 64, g1k(n, cl) * 64, sb + BAR_FULL + n * 8, maskW1);
            }
            const int k2 = rowPos < rowStep ? N_CP + ((rowPos - N_CP) & (rowStep - 1)) : N_ALL;
#pragma unroll 1
            for (int k = k2; k < N_CP + W2_AHEAD; k += rowStep) w2_prefetch(&mW2, k - N_CP + cl * 4, tb);
#pragma unroll 1
            for (int k = colPos < 2 ? colPos : N_CP; k < N_CP; k += 2) {
                const int n = k + N_G1;
                mbar_wait0(sb + BAR_EMPTY + n * 8, spin);
                PROF_E(0, n);
                tma2d_mc(sb + ((n + 7) & 7) * SLOT_BYTES, k >= 7 ? &mCim : &mCre, (k >= 7 ? k - 7 : k) * 64, sl * 64, sb + BAR_FULL + n * 8, colMask);
            }
#pragma unroll 1
            for (int k = k2; k < N_CP + N_G2; k += rowStep) {
                const int n = k + N_G1;
                const int kf = k - N_CP + cl * 4;
                mbar_wait0(sb + BAR_EMPTY + n * 8, spin);
                PROF_E(0, n);
                tma3d_mc(sb + ((n + 7) & 7) * SLOT_BYTES + 8192, &mW2, 0, (kf >= N_G2 ? kf - N_G2 : kf) * 64, tb * 2, sb + BAR_FULL + n * 8, rowMask);
                if (k + W2_AHEAD < N_CP + N_G2) w2_prefetch(&mW2, kf + W2_AHEAD, tb);
            }
        }
    } else if (warp == 9) {
        if (lane < 7) mbar_expect_tx(sb + BAR_BU + lane * 8, 32768);
        {
            const char* bRows = (const char*)(rank < 8 ? p.bre : p.bim) + (cl * 64 + (rank & 7) * 8 + i8) * 896 + c4 * 16;
            uint4 v[14];
            spin_until(t_start + B_LATE);
#pragma unroll
            for (int i = 0; i < 14; i++) v[i] = __ldg((const uint4*)(bRows + i * 64));
            float d[4][4];
#pragma unroll
            for (int i = 0; i < 16; i++) d[i >> 2][i & 3] = 0.f;
#pragma unroll
            for (int i = 0; i < 14; i++) {
                mma_ones(d[(i & 1) * 2], v[i].x, v[i].y);
                mma_ones(d[(i & 1) * 2 + 1], v[i].z, v[i].w);
            }
            const float s0 = (d[0][0] + d[1][0]) + (d[2][0] + d[3][0]), s1 = (d[0][1] + d[1][1]) + (d[2][1] + d[3][1]);
            nb_arrive(7 + (__float_as_uint(s0) & p.zero), 480);
            if (lane == 0 && s0 != -1.2345e30f) PROF_T(24);
            mbar_wait0(sb + BAR_RDY, spin);
#pragma unroll
            for (int z = 0; z < 2; z++)
                st_async2(mapa(sb + AUX_BSUM + rank * 32 + c4 * 8, i8 + z * 8), s0, s1, mapa(sb + BAR_BS, i8 + z * 8));
            const char* pf = (const char*)p.w1 + (rank * 8 + i8) * 3584 + cl * 512 + c4 * 128;
            spin_until(t_start + PF_START);
#pragma unroll 1
            for (int j = 0; j < PF_N0; j++) {
                l2_prefetch_line(pf + g1k(2 * j, cl) * (64 * 3584));
                if (PF_NS) __nanosleep(PF_NS);
            }
            cluster_wait();
            const char* src = (const char*)p.s->hn + di * 14336;
#pragma unroll 1
            for (int i = 0; i < 8; i++) {
                const int n = fi + 4 * i;
                mbar_wait0(sb + BAR_EMPTY + n * 8, spin);
                if (elect_one()) {
                    bulk_mc(sb + 8192 + slot_off(n), src + g1k(n, cl) * 57344, 14336, sb + BAR_FULL + n * 8, (uint16_t)(0x1111u << di));
                    PROF_E(3, n);
                }
                __syncwarp();
                if (i < (16 - PF_N0) / 2) {
                    l2_prefetch_line(pf + g1k(2 * PF_N0 + 4 * i, cl) * (64 * 3584));
                    l2_prefetch_line(pf + g1k(2 * PF_N0 + 2 + 4 * i, cl) * (64 * 3584));
                } else if (i == (16 - PF_N0) / 2 && lane < 28) {
                    l2_prefetch_line((const char*)p.cre + (cta * 28 + lane) * 128);
                    l2_prefetch_line((const char*)p.cim + (cta * 28 + lane) * 128);
                }
            }
        }
        if (elect_one()) {
            if (rowPos < rowStep)
                bulk_run(sb, N_G1 + rowPos, N_G1 + N_CP, rowStep, (const char*)p.s->H + (tb * 14 + rowPos * 2) * 16384, rowStep * 32768,
                         N_G1 + 7, -13 * 16384, 8192, 16384, rowMask, spin PROF_ARG);
            if (colPos < 2)
                bulk_run(sb, N_G1 + N_CP + colPos, N_ALL, 2, (const char*)p.s->U + sl * 8192 + (colPos + cl * 4) * 57344, 2 * 57344,
                         N_ALL - cl * 4, -N_G2 * 57344, 0, 8192, colMask, spin PROF_ARG);
        }
    } else if (warp < 4 || warp >= 12) {
        const int w = warp & 3, hh = warp >> 3, t7 = tid & 127;
        const uint32_t buAddr = t7 < 18 ? mapa(sb + BAR_EMPTY + (t7 >> 1) * 8, issuer(t7 >> 1, t7 & 1)) : (t7 < 48 ? mapa(sb + BAR_K6, t7 & 15) : sb + BAR_K0);
        const int buK = t7 < 16 ? (0x66544322 >> ((t7 >> 1) * 4)) & 7 : (t7 < 18 ? 6 : ((t7 >> 5) == 1 ? 0 : -2));
        if (hh == 0) {
            nb_sync(1, 160);
            if (warp == 3) {
                if (lane < CS) mbar_arrive_cluster(mapa(sb + BAR_RDY, lane));
                if (lane == 0) {
                    asm volatile("prefetch.tensormap [%0];" ::"l"(&mW1) : "memory");
                    asm volatile("prefetch.tensormap [%0];" ::"l"(&mCre) : "memory");
                    asm volatile("prefetch.tensormap [%0];" ::"l"(&mCim) : "memory");
                    asm volatile("prefetch.tensormap [%0];" ::"l"(&mW2) : "memory");
                    asm volatile("prefetch.tensormap [%0];" ::"l"(&mOut) : "memory");
                }
            } else {
                const int n = tid;
                int pend = 0;
                if (n < N_ALL) {
                    mbar_expect_tx(sb + BAR_FULL + n * 8, n < N_G1 ? 8192 + 14336 : SLOT_BYTES);
                    const bool ia = issuer(n, 0) == rank, ib = issuer(n, 1) == rank;
                    const int c = 32 - ((ia ? (n < N_G1 ? 4 : colSize) : 0) + (ib ? (n < N_G1 ? 4 : rowSize) : 0)) * (n < NSLOT1 ? 2 : 1);
                    if ((ia && n >= N_G1 + N_CP && n < N_G1 + N_CP + 4) || (ib && n < 4)) mbar_arrive_n(sb + BAR_EMPTY + n * 8, c - (n >= 4 ? 16 : 8));
                    else if (n < N_G1 + N_CP ? ib : ia) pend = c;
                    else if (c < 32) mbar_arrive_n(sb + BAR_EMPTY + n * 8, c);
                } else if (n < N_ALL + 3) {
                    mbar_expect_tx(sb + BAR_FULL + n * 8, n == N_ALL + 2 ? 512 : rank * 256);
                }
                smem[PARAM_OFF + 1024 + n] = (unsigned char)pend;
            }
#pragma unroll
            for (int z = 0; z < 4; z++) *(uint4*)(smem + RCV_OFF + z * 2048 + tid * 16) = make_uint4(0u, 0u, 0u, 0u);
            nb_arrive(6, 256);
        } else if (warp >= 14) {
            const int st = cl * 64 + tid - 448;
            *(float4*)(smem + PARAM_OFF + (tid - 448) * 16) = state_params(ldbf(p.lre + st), ldbf(p.lim + st), ldbf(p.ldt + st));
            nb_arrive(6, 256);
        }
        if (tid == 0) PROF_T(29);
        float acc[64];
        {
            uint64_t dA = mkdesc(sb + hh * 8192, 16, 1024, 1);
            const uint32_t ob = 1024 - hh * 512;
            nb_sync(7, 480);
            mbar_wait0(sb + BAR_RDY, spin);
            mbar_wait0(sb + BAR_BU, spin);
            if (tid == 0) PROF_T(0);
#pragma unroll 1
            for (int k = 0; k < 7; k++) {
                const uint64_t dB = dA + ob;
                wg_fence();
                wgmma_n128<0, 0>(acc, dA, dB, k);
                wgmma_n128<0, 0>(acc, dA + 2, dB + 2, 1);
                wg_commit();
                wg_wait<1>();
                if (buK == k - 1) mbar_arrive_cluster(buAddr);
                const bool ok = mbar_test(sb + BAR_BU + k * 8 + 8);
                wgmma_n128<0, 0>(acc, dA + 4, dB + 4, 1);
                wgmma_n128<0, 0>(acc, dA + 6, dB + 6, 1);
                wg_commit();
                dA += k == 5 ? -5 * 2048 : 2048;
                if (!ok) mbar_wait0(sb + BAR_BU + k * 8 + 8, spin);
            }
            nb_sync(8, 288);
            mbar_wait0(sb + BAR_BS, spin);
            nb_sync(2, 320);
            const int sk = hh * 32 + w * 8 + i8;
            const float bsr = -*(const float*)(smem + AUX_BSUM + sk * 4), bsi = -*(const float*)(smem + AUX_BSUM + 256 + sk * 4);
            const float4 sp = *(const float4*)(smem + PARAM_OFF + sk * 16);
            const float2 lam = make_float2(sp.x, sp.y);
            unsigned char* xch = smem + STAGE_OFF + (hh * 4 + w) * 1024 + (w & 1) * 64 + c4 * 64 + i8 * 8;
            float4 st0[PRE];
#pragma unroll
            for (int j = 0; j < PRE; j++) {
                const int jj = (j & 1) * 8 + (j >> 1);
                st0[j] = lds128(sb + AUX_STAT + ((jj >> 3) * 4 + c4) * 144 + (jj & 7) * 16);
            }
            wg_wait<0>();
            pin(acc);
            if (buK == 6) mbar_arrive_cluster(buAddr);
            if (tid == 0) PROF_T(1);
            float2 h[2] = {make_float2(0.f, 0.f), make_float2(0.f, 0.f)};
#pragma unroll
            for (int j = 0; j < 16; j++) {
                const int jj = (j & 1) * 8 + (j >> 1);
                const float4 st = j < PRE ? st0[j < PRE ? j : 0] : *(const float4*)(smem + AUX_STAT + ((jj >> 3) * 4 + c4) * 144 + (jj & 7) * 16);
#pragma unroll
                for (int e = 0; e < 2; e++) {
                    const float r = e ? st.z : st.x, mr = e ? st.w : st.y;
                    const int a = 4 * jj + e;
                    acc[a] = fmaf(r, acc[a], mr * bsr);
                    acc[a + 2] = fmaf(r, acc[a + 2], mr * bsi);
                    h[jj >> 3] = cfma(lam, h[jj >> 3], make_float2(acc[a], acc[a + 2]));
                }
            }
            *(float2*)(xch) = h[0];
            *(float2*)(xch + 256) = h[1];
            __syncwarp();
            if (lane == 0) mbar_arrive_n(sb + BAR_P1, 4);
            if (tid == 0) PROF_T(2);
            pin(acc);
            mbar_wait0(sb + BAR_RDY, spin);
            float nw = -sp.w, lnk = 0.f;
#pragma unroll
            for (int a = 0; a < 64; a++) {
                if ((a & 2) == 0) {
                    if (LINK && ((a >> 2) * 2 + (a & 1)) % LINK == 0) nw = __uint_as_float(__float_as_uint(nw) ^ (__float_as_uint(lnk) & p.zero));
                    const float tr = fmaf(sp.z, acc[a], nw * acc[a + 2]);
                    acc[a + 2] = fmaf(-sp.z, acc[a + 2], nw * acc[a]);
                    acc[a] = tr;
                    lnk = tr;
                }
            }
            pin(acc);
            mbar_wait0(sb + BAR_RDY, spin);
            nb_sync(9 + hh, 160);
            h[0] = *(const float2*)(xch);
            h[1] = *(const float2*)(xch + 256);
            __syncwarp();
            const float2 la2 = make_float2(lam.x, -lam.y);
#pragma unroll
            for (int a = 0; a < 2; a++) h[a] = make_float2(fmaf(sp.z, h[a].x, -sp.w * h[a].y), fmaf(-sp.z, h[a].y, -sp.w * h[a].x));
            uint32_t hI[4][4];
#pragma unroll
            for (int q = 0; q < 4; q++) {
                const int q4 = (q & 1) * 2 + (q >> 1);
                uint32_t oR[4];
                uint32_t (&oI)[4] = hI[q4];
                float2& hc = h[q4 >> 1];
#pragma unroll
                for (int z = 0; z < 4; z++) {
                    const int a = 4 * (q4 * 4 + z);
                    const float2 h0 = cfma(la2, hc, make_float2(acc[a], acc[a + 2]));
                    hc = cfma(la2, h0, make_float2(acc[a + 1], acc[a + 3]));
                    oR[z] = pack_bf16(h0.x, hc.x);
                    oI[z] = pack_bf16(h0.y, hc.y);
                }
                const int off = STAGE_OFF + (q4 >> 1) * 8192 + sk * 128 + (((c4 * 2 + (q4 & 1)) ^ i8) * 16);
                *(uint4*)(smem + off) = make_uint4(oR[0], oR[1], oR[2], oR[3]);
            }
            fence_async_smem();
            __syncwarp();
            if (tid == 0) PROF_T(4);
            {
                const int blk = (hh * 4 + w) * 1024;
                char* dstH = (char*)p.s->H + (rank * 14 + cl * 2) * 16384 + blk;
                uint32_t tH = (uint32_t)clock64() + (hh * 4 + w) * H_CYC;
#pragma unroll 1
                for (int part = 0; part < 2; part++) {
                    while ((int)((uint32_t)clock64() - tH) < 0) __nanosleep(32);
                    tH += H_GAP + (hh * 4 + w) * (H_CYC2 - H_CYC);
                    if (elect_one()) {
                        bulk_store(dstH, sb + STAGE_OFF + blk, 1024);
                        bulk_store(dstH + 8192, sb + STAGE_OFF + blk + 8192, 1024);
                        bulk_commit();
                        bulk_wait_all();
                    }
                    __syncwarp();
                    if (part) nb_arrive(15, 384);
                    unsigned rb[1];
                    rb[0] = ld_relaxed((const unsigned*)(dstH + ((lane >> 3) & 1) * 8192 + (lane & 7) * 128));
                    if (!part) {
#pragma unroll
                        for (int q4 = 0; q4 < 4; q4++)
                            *(uint4*)(smem + STAGE_OFF + (q4 >> 1) * 8192 + sk * 128 + (((c4 * 2 + (q4 & 1)) ^ i8) * 16)) =
                                make_uint4(hI[q4][0], hI[q4][1], hI[q4][2], hI[q4][3]);
                    }
                    bump(rb, &p.s->cnt[(CNT_H + rank * 2 + part) * 32], p.zero);
                    fence_async_smem();
                    __syncwarp();
                    if (tid == 480) { if (part) PROF_T(5); else PROF_T(30); }
                    dstH += 16384;
                }
            }
            cluster_wait();
        }
        if (hh == 0) {
            const int relUse = tid < 68 ? (tid >> 1) + N_G1 : 0;
            const uint32_t relAddr = mapa(sb + BAR_EMPTY + (relUse + NSLOT) * 8, issuer(relUse + NSLOT, tid & 1));
            uint32_t aRes = sb + RES_OFF + ((lane >> 4) * 8 + (lane & 7)) * 128 + (((w * 2 + ((lane >> 3) & 1)) ^ (lane & 7)) * 16);
            const int dl = (w & 1) * 16 + i8;
            uint32_t aOut = sb + OUT_OFF + (w >> 1) * 16384 + (dl & 3) * 4 + c4 * 256 + (((dl >> 2) ^ (c4 * 2)) * 16);
            uint32_t cX = sl * 64 + (w >> 1) * 32, cY = tb * 128, aTma = sb + OUT_OFF + (w >> 1) * 16384;
            aRes = launder(aRes, p.zero); aOut = launder(aOut, p.zero);
            cX = launder(cX, p.zero); cY = launder(cY, p.zero); aTma = launder(aTma, p.zero);
            mma_run<1>(acc, sb, N_G1, N_G1 + N_CP, relUse, relAddr, spin);
            if (tid == 0) PROF_T(19);
            mma_run<2>(acc, sb, N_G1 + N_CP, N_ALL, relUse, relAddr, spin);
            nb_sync(13, 256);
            uint32_t rf[32];
#pragma unroll
            for (int j2 = 0; j2 < 8; j2++) {
                asm volatile("ldmatrix.sync.aligned.m8n8.x4.trans.shared.b16 {%0, %1, %2, %3}, [%4];"
                             : "=r"(rf[4 * j2]), "=r"(rf[4 * j2 + 1]), "=r"(rf[4 * j2 + 2]), "=r"(rf[4 * j2 + 3]) : "r"(aRes + j2 * 2048) : "memory");
            }
            wg_wait<0>();
            pin(acc);
            if (tid == 0) PROF_T(9);
#pragma unroll
            for (int part = 0; part < OUT_PARTS; part++) {
#pragma unroll
                for (int jj = part * (16 / OUT_PARTS); jj < (part + 1) * (16 / OUT_PARTS); jj++) {
                    sts32(aOut + jj * 1024, acc[4 * jj] + bf_lo(rf[2 * jj]));
                    sts32((aOut ^ 16) + 128 + jj * 1024, acc[4 * jj + 1] + bf_hi(rf[2 * jj]));
                    sts32((aOut ^ 32) + jj * 1024, acc[4 * jj + 2] + bf_lo(rf[2 * jj + 1]));
                    sts32((aOut ^ 48) + 128 + jj * 1024, acc[4 * jj + 3] + bf_hi(rf[2 * jj + 1]));
                }
                fence_async_smem();
                nb_sync(4 + (w >> 1), 64);
                if ((tid & 63) == 0) {
                    tma2d_store(&mOut, cX, cY + part * (128 / OUT_PARTS), aTma + part * (16384 / OUT_PARTS));
                    if (part == OUT_PARTS - 1) bulk_commit();
                }
                if (part == 0) {
                    pin(acc);
                    mbar_wait0(sb + BAR_RDY, spin);
                }
            }
            if (tid == 0 && cta == 0) p.s->epoch[0] = *(const unsigned*)(smem + AUX_EPOCH);
            if ((tid & 63) == 0) bulk_wait_read();
        }
    } else if (warp < 8) {
        const int w = warp - 4;
        float acc[56];
#pragma unroll
        for (int j = 0; j < 14; j++) {
            acc[4 * j] = acc[4 * j + 1] = 0.5f * bias0;
            acc[4 * j + 2] = acc[4 * j + 3] = 0.5f * bias1;
        }
        pin(acc);
        cluster_wait();
        const int relT = min(NSLOT1 + ((tid - 128) >> 1), N_G1 + NSLOT);
        const int relUse = relT < N_G1 ? relT - NSLOT1 : (relT == N_G1 ? 24 : (relT < N_G1 + NSLOT ? min(relT - 7, N_G1 - 1) : 99));
        const uint32_t relAddr = mapa(sb + BAR_EMPTY + relT * 8, issuer(relT, tid & 1));
        mbar_wait0(sb + BAR_RDY, spin);
        mma_run<0>(acc, sb, 0, N_G1, relUse, relAddr, spin);
        wg_wait<0>();
        pin(acc);
        if (relUse == N_G1 - 1) mbar_arrive_cluster(relAddr);
        if (tid == 128) PROF_T(12);
        char* dstU = (char*)p.s->U + (fb * 56 + di * 14) * 1024 + w * 256 + lane * 4;
        const uint32_t own = mapa(sb + BAR_EMPTY + (N_G1 + N_CP + fi) * 8, min(lane, 6) + 7 * (fi & 1));
#pragma unroll
        for (int j = 0; j < 14; j++) {
            *(uint32_t*)(dstU + j * 1024) = pack_bf16(gelu_half(acc[4 * j + 0]), gelu_half(acc[4 * j + 1]));
            *(uint32_t*)(dstU + j * 1024 + 128) = pack_bf16(gelu_half(acc[4 * j + 2]), gelu_half(acc[4 * j + 3]));
            if (j == 3 && lane == 0) mbar_arrive_n(sb + BAR_CP, 8);
            if (j == 3 || j == 7) {
                pin(acc);
                mbar_wait0(sb + BAR_RDY, spin);
            }
        }
        if (tid == 128) PROF_T(13);
        fence_async_global();
        {
            unsigned rb[1];
            rb[0] = ld_relaxed((const unsigned*)(dstU + (min(lane, 27) >> 1) * 1024 + (lane & 1) * 128));
            const unsigned z = bump(rb, &p.s->cnt[(CNT_U + fb) * 32], p.zero);
            if (lane < 7) mbar_arrive_cluster(own + z);
        }
        if (tid == 128) PROF_T(15);
        {
            const int t = tid - 128, ch = t & 7, r0 = t >> 3;
            const uint4 dk = __ldg((const uint4*)(p.dsk + sl * 64 + ch * 8));
            const char* xp = (const char*)p.x + (tb * 128 + r0) * 896 + sl * 128 + ch * 16;
            const unsigned short* bp = (const unsigned short*)p.b2 + tb * 128 + r0;
            uint4* rs = (uint4*)(smem + RES_OFF + r0 * 128 + ((ch ^ (r0 & 7)) * 16));
            nb_sync(15, 384);
#pragma unroll 2
            for (int it = 0; it < 8; it++) {
                const uint4 xv = __ldg((const uint4*)(xp + it * (16 * 896)));
                const uint32_t b2 = (uint32_t)__ldg(bp + it * 16) * 0x10001u;
                const uint4 su = __ldcg(&p.s->stat[tb * 128 + it * 16 + r0]);
                const float nm = -__fdividef(__uint_as_float(su.z), __uint_as_float(su.x));
                const uint32_t r2 = pack_bf16(__uint_as_float(su.x), __uint_as_float(su.x)), m2 = pack_bf16(nm, nm);
                auto res = [&](uint32_t x2, uint32_t d2) { return hadd2(hfma2(hmul2(hadd2(x2, m2), r2), d2, b2), x2); };
                rs[it * 128] = make_uint4(res(xv.x, dk.x), res(xv.y, dk.y), res(xv.z, dk.z), res(xv.w, dk.w));
            }
            nb_arrive(13, 256);
            if (tid == 128) PROF_T(6);
        }
    } else {
        const int hh = warp - 10;
        const unsigned ep = ld_relaxed(p.s->epoch) + 1u;
        if (sl >= 2) nb_arrive(7, 480);
        nb_sync(6, 256);
        const float4 hsp = lds128(sb + PARAM_OFF + (hh * 32 + lane) * 16);
        if (hh == 0) {
            if (lane == 0) PROF_T(3);
            uint4 a[4];
            spin_until(t_start + STAT_START);
            while (true) {
                unsigned tags = 0;
#pragma unroll
                for (int c = 0; c < 4; c++) a[c] = ld_ll(&p.s->stat[rank * 128 + c * 32 + lane]);
#pragma unroll
                for (int c = 0; c < 4; c++) tags += a[c].y + a[c].w;
                if (__all_sync(0xffffffffu, tags == 8u * ep)) break;
                if (++spin > SPIN_LIMIT) __trap();
            }
#pragma unroll
            for (int c = 0; c < 4; c++) *(uint2*)(smem + AUX_STAT + (c * 2 + (lane >> 4)) * 144 + (lane & 15) * 8) = make_uint2(a[c].x, a[c].z);
            if (lane == 0) *(unsigned*)(smem + AUX_EPOCH) = ep;
            nb_arrive(8, 288);
            if (sl < 2) bump(rb3, &p.s->cnt[(CNT_LN + 28 + (tb >> 2)) * 32], p.zero);
            if (lane == 0) PROF_T(23);
        }
        if (hh == 1) spin_until(t_start + PREP_START);
        float2 pw[8], l128;
        pw[1] = make_float2(hsp.x, hsp.y);
#pragma unroll
        for (int z = 0; z < 4; z++) pw[1] = cmul(pw[1], pw[1]);
#pragma unroll
        for (int j = 2; j < 8; j++) pw[j] = cmul(pw[j - 1], pw[1]);
        l128 = cmul(pw[4], pw[4]);
        pw[0] = cmul(l128, l128);
        pw[0] = cmul(cmul(pw[0], pw[0]), l128);
        const uint32_t rcv = RCV_OFF + hh * 4096;
        uint32_t dst[8], dbar[8];
        {
            const uint32_t d0 = sb + rcv + (lane & 15) * 16 + (14 - (lane >> 4)) * 256 + ((1 + (lane >> 4)) << 24);
            const uint32_t b0 = sb + BAR_FN + hh * 8 + ((1 + (lane >> 4)) << 24);
            const int left = 15 - rank - (lane >> 4);
#pragma unroll
            for (int j = 0; j < 8; j++) {
                dst[j] = 2 * j < left ? d0 + j * ((2 << 24) - 512) : sb + AUX_STAT + (lane & 15) * 16;
                dbar[j] = 2 * j < left ? b0 + j * (2 << 24) : sb + BAR_NIL;
                asm volatile("" : "+r"(dst[j]), "+r"(dbar[j]));
            }
        }
        pin2(pw);
        int pend[3];
        if (hh == 1) {
#pragma unroll
            for (int r = 0; r < 3; r++) pend[r] = smem[PARAM_OFF + 1024 + r * 32 + lane];
            if (lane == 0 && pend[0] < 1000) PROF_T(21);
            poll_round(&p.s->cnt[(CNT_LN + g1k(lane, cl)) * 32], ep * 8u, lane < 28 ? pend[0] : 0, sb + BAR_EMPTY + lane * 8, spin);
            if (lane == 0) PROF_T(20);
        }
        {
            float2* xch = (float2*)(smem + STAGE_OFF + (hh * 4 + (lane >> 3)) * 1024 + ((lane >> 3) & 1) * 64 + (lane & 7) * 8);
            mbar_wait0(sb + BAR_P1, spin);
            float2 run[8];
#pragma unroll
            for (int j = 0; j < 8; j++) run[j] = xch[j * 8];
            float2 cy = cfma(pw[4], cfma(pw[2], cfma(pw[1], run[0], run[1]), cfma(pw[1], run[2], run[3])),
                             cfma(pw[2], cfma(pw[1], run[4], run[5]), cfma(pw[1], run[6], run[7])));
            {
                const int s0 = (lane & 15) * 2;
                const float a0 = __shfl_sync(0xffffffffu, cy.x, s0), a1 = __shfl_sync(0xffffffffu, cy.y, s0);
                const float a2 = __shfl_sync(0xffffffffu, cy.x, s0 + 1), a3 = __shfl_sync(0xffffffffu, cy.y, s0 + 1);
#pragma unroll
                for (int j = 0; j < 8; j++)
                    asm volatile("st.async.shared::cluster.mbarrier::complete_tx::bytes.v4.f32 [%0], {%1, %2, %3, %4}, [%5];"
                                 ::"r"(dst[j]), "f"(a0), "f"(a1), "f"(a2), "f"(a3), "r"(dbar[j]) : "memory");
            }
#pragma unroll
            for (int j = 1; j < 7; j++) run[j] = cfma(pw[1], run[j - 1], run[j]);
            pin2(run);
            mbar_wait0(sb + BAR_FN + hh * 8, spin);
            float2 f[15];
#pragma unroll
            for (int i = 0; i < 15; i++) f[i] = *(const float2*)(smem + rcv + i * 256 + lane * 8);
            float2 c0 = f[0], c1 = f[5], c2 = f[10];
#pragma unroll
            for (int i = 1; i < 5; i++) {
                c0 = cfma(l128, c0, f[i]);
                c1 = cfma(l128, c1, f[5 + i]);
                c2 = cfma(l128, c2, f[10 + i]);
            }
            cy = cfma(pw[0], cfma(pw[0], c0, c1), c2);
            xch[0] = cy;
#pragma unroll
            for (int j = 1; j < 8; j++) xch[j * 8] = cfma(pw[j], cy, run[j - 1]);
            nb_arrive(9 + hh, 160);
            if (hh == 1 && lane == 0) PROF_T(7);
        }
        if (hh == 1) {
#pragma unroll 1
            for (int r = 0; r < 3; r++) {
                const int n = r * 32 + lane;
                int kf = n - N_G1 - N_CP + cl * 4;
                if (kf >= N_G2) kf -= N_G2;
                const bool isH = n < N_G1 + N_CP;
                poll_round(&p.s->cnt[(r == 0 ? CNT_LN + lane : (isH ? CNT_H + tb * 2 + (n >= N_G1 + 7) : CNT_U + min(kf, N_G2 - 1))) * 32],
                           ep * (r == 0 ? 8u : (isH ? 56u : 16u)),
                           r == 0 ? (lane < 28 ? 0 : pend[0]) : (r == 1 ? pend[1] : pend[2]), sb + BAR_EMPTY + n * 8, spin);
                if (lane == 0 && r == 1) PROF_T(22);
            }
        }
        cluster_wait();
    }
}

struct FbScratch {
    float xn[S_ * D_], hn[S_ * D_], G[S_ * 2 * D_], U[D_ * F_];
};
__device__ FbScratch g_fb;

__global__ void fb_ln(const Params p) {
    const int row = blockIdx.x * 8 + (threadIdx.x >> 5), lane = threadIdx.x & 31;
    float v[14], s = 0.f;
    for (int i = 0; i < 14; i++) { v[i] = ldbf(p.x + row * D_ + i * 32 + lane); s += v[i]; }
    for (int pass = 0; pass < 2; pass++) {
        for (int o = 16; o; o >>= 1) s += __shfl_xor_sync(0xffffffffu, s, o);
        const float m = s / D_;
        float q = 0.f;
        for (int i = 0; i < 14; i++) q += (v[i] - m) * (v[i] - m);
        for (int o = 16; o; o >>= 1) q += __shfl_xor_sync(0xffffffffu, q, o);
        const float r = rsqrtf(q / D_ + 1e-5f);
        s = 0.f;
        for (int i = 0; i < 14; i++) {
            v[i] = (v[i] - m) * r;
            s += v[i];
            (pass ? g_fb.hn : g_fb.xn)[row * D_ + i * 32 + lane] = v[i];
        }
    }
}
template <int MODE>
__global__ void fb_gemm(const Params p) {
    __shared__ float sa[16][33], sb[16][33];
    const int tx = threadIdx.x & 15, ty = threadIdx.x >> 4, m0 = blockIdx.y * 32, n0 = blockIdx.x * 32;
    constexpr int K = MODE == 0 ? D_ : (MODE == 1 ? S_ : F_ + 2 * D_);
    float c[2][2] = {{0.f, 0.f}, {0.f, 0.f}};
    for (int k0 = 0; k0 < K; k0 += 16) {
        for (int e = threadIdx.x; e < 512; e += 256) {
            const int kk = e >> 5, i = e & 31, k = k0 + kk, m = m0 + i, n = n0 + i;
            if (MODE == 0) {
                sa[kk][i] = g_fb.xn[m * D_ + k];
                sb[kk][i] = ldbf((n < D_ ? p.bre + n * D_ : p.bim + (n - D_) * D_) + k);
            } else if (MODE == 1) {
                sa[kk][i] = g_fb.hn[k * D_ + m];
                sb[kk][i] = ldbf(p.w1 + k * F_ + n);
            } else if (k < F_) {
                sa[kk][i] = ldbf(p.w2 + k * S_ + m);
                sb[kk][i] = g_fb.U[n * F_ + k];
            } else {
                const int q = k - F_;
                sa[kk][i] = g_fb.G[m * 2 * D_ + q];
                sb[kk][i] = q < D_ ? ldbf(p.cre + n * D_ + q) : -ldbf(p.cim + n * D_ + q - D_);
            }
        }
        __syncthreads();
        for (int kk = 0; kk < 16; kk++)
            for (int i = 0; i < 2; i++)
                for (int j = 0; j < 2; j++) c[i][j] = fmaf(sa[kk][ty + 16 * i], sb[kk][tx + 16 * j], c[i][j]);
        __syncthreads();
    }
    for (int i = 0; i < 2; i++)
        for (int j = 0; j < 2; j++) {
            const int m = m0 + ty + 16 * i, n = n0 + tx + 16 * j;
            if (MODE == 0) g_fb.G[m * 2 * D_ + n] = c[i][j];
            else if (MODE == 1) g_fb.U[m * F_ + n] = gelu_half(0.5f * (c[i][j] + ldbf(p.b1 + n)));
            else p.out[m * D_ + n] = c[i][j] + ldbf(p.x + m * D_ + n) + g_fb.xn[m * D_ + n] * ldbf(p.dsk + n) + ldbf(p.b2 + m);
        }
}
__global__ void fb_scan(const Params p) {
    const int s = blockIdx.x * 32 + threadIdx.x;
    const float4 sp = state_params(ldbf(p.lre + s), ldbf(p.lim + s), ldbf(p.ldt + s));
    float2 h = make_float2(0.f, 0.f);
    for (int t = 0; t < S_; t++) {
        float* g = g_fb.G + t * 2 * D_ + s;
        h = cfma(make_float2(sp.x, sp.y), h, cmul(make_float2(sp.z, sp.w), make_float2(g[0], g[D_])));
        g[0] = h.x;
        g[D_] = h.y;
    }
}

typedef CUresult (*EncodeFn)(CUtensorMap*, CUtensorMapDataType, cuuint32_t, void*, const cuuint64_t*, const cuuint64_t*,
                             const cuuint32_t*, const cuuint32_t*, CUtensorMapInterleave, CUtensorMapSwizzle,
                             CUtensorMapL2promotion, CUtensorMapFloatOOBfill);

bool encode(EncodeFn fn, CUtensorMap* m, CUtensorMapDataType dt, int rank, const void* ptr, const cuuint64_t* dims,
            const cuuint64_t* strides, const cuuint32_t* box, CUtensorMapSwizzle sw = CU_TENSOR_MAP_SWIZZLE_128B) {
    cuuint32_t es[5] = {1, 1, 1, 1, 1};
    if (!fn) return false;
    return fn(m, dt, rank, (void*)ptr, dims, strides, box, es, CU_TENSOR_MAP_INTERLEAVE_NONE, sw,
              CU_TENSOR_MAP_L2_PROMOTION_L2_128B, CU_TENSOR_MAP_FLOAT_OOB_FILL_NONE) == CUDA_SUCCESS;
}

}

extern "C" void kernel_launch(void* const* d_in, const int* in_sizes, int n_in, void* d_out, int out_size) {
    (void)in_sizes; (void)n_in; (void)out_size;
    typedef const __nv_bfloat16* bp;
    Params p;
    p.x = (bp)d_in[0]; p.lre = (bp)d_in[1]; p.lim = (bp)d_in[2]; p.bre = (bp)d_in[3]; p.bim = (bp)d_in[4];
    p.cre = (bp)d_in[5]; p.cim = (bp)d_in[6]; p.ldt = (bp)d_in[7]; p.dsk = (bp)d_in[8];
    void* sp = nullptr;
    cudaGetSymbolAddress(&sp, g_s);
    p.s = (Scratch*)sp;
    p.out = (float*)d_out;
    p.zero = 0;
    p.w1 = (bp)d_in[10]; p.b1 = (bp)d_in[11]; p.w2 = (bp)d_in[12]; p.b2 = (bp)d_in[13];

    void* f = nullptr;
    cudaDriverEntryPointQueryResult qr;
    cudaGetDriverEntryPoint("cuTensorMapEncodeTiled", &f, cudaEnableDefault, &qr);
    EncodeFn fn = (EncodeFn)f;
    CUtensorMap mX, mBre, mBim, mW1, mCre, mCim, mW2, mHn, mOut;
    const CUtensorMapDataType BF = CU_TENSOR_MAP_DATA_TYPE_BFLOAT16;
    bool ok = true;
    {
        cuuint64_t d[5] = {448, 2, 4, 8, 32}, s[4] = {896, 16 * 896, 2 * 896, 64 * 896};
        cuuint32_t b[5] = {64, 2, 4, 8, 2};
        ok &= encode(fn, &mX, BF, 5, p.x, d, s, b);
    }
    {
        cuuint64_t d[2] = {448, 448}, s[1] = {896};
        cuuint32_t b[2] = {64, 64};
        cuuint32_t b8[2] = {64, 8};
        ok &= encode(fn, &mBre, BF, 2, p.bre, d, s, b8);
        ok &= encode(fn, &mBim, BF, 2, p.bim, d, s, b8);
        ok &= encode(fn, &mCre, BF, 2, p.cre, d, s, b);
        ok &= encode(fn, &mCim, BF, 2, p.cim, d, s, b);
    }
    {
        cuuint64_t d[2] = {1792, 2048}, s[1] = {3584};
        cuuint32_t b[2] = {64, 64};
        ok &= encode(fn, &mW1, BF, 2, p.w1, d, s, b);
    }
    {
        cuuint64_t d[3] = {64, 1792, 32}, s[2] = {4096, 128};
        cuuint32_t b[3] = {64, 64, 2};
        ok &= encode(fn, &mW2, BF, 3, p.w2, d, s, b);
    }
    {
        cuuint64_t d[2] = {448, 2048}, s[1] = {1792};
        cuuint32_t b[2] = {32, 128 / OUT_PARTS};
        ok &= encode(fn, &mOut, CU_TENSOR_MAP_DATA_TYPE_FLOAT32, 2, d_out, d, s, b);
    }
    {
        cuuint64_t d[2] = {512, 1792}, s[1] = {1024};
        cuuint32_t b[2] = {64, 56};
        ok &= encode(fn, &mHn, BF, 2, p.s->hn, d, s, b);
    }
    cudaFuncSetAttribute(fused_kernel, cudaFuncAttributeMaxDynamicSharedMemorySize, SMEM_BYTES);
    cudaFuncSetAttribute(fused_kernel, cudaFuncAttributeNonPortableClusterSizeAllowed, 1);
    cudaLaunchConfig_t cfg = {};
    cfg.gridDim = dim3(NCTA);
    cfg.blockDim = dim3(512);
    cfg.dynamicSmemBytes = SMEM_BYTES;
    cfg.stream = cudaStreamPerThread;
    cudaLaunchAttribute at[1];
    at[0].id = cudaLaunchAttributeClusterDimension;
    at[0].val.clusterDim.x = CS;
    at[0].val.clusterDim.y = 1;
    at[0].val.clusterDim.z = 1;
    cfg.attrs = at;
    cfg.numAttrs = 1;
    int nClusters = 0;
    if (cudaOccupancyMaxActiveClusters(&nClusters, fused_kernel, &cfg) != cudaSuccess) nClusters = 0;
    if (!ok || nClusters < NCL) {
        (void)cudaGetLastError();
        cudaStream_t st = cudaStreamPerThread;
        fb_ln<<<S_ / 8, 256, 0, st>>>(p);
        fb_gemm<0><<<dim3(2 * D_ / 32, S_ / 32), 256, 0, st>>>(p);
        fb_scan<<<D_ / 32, 32, 0, st>>>(p);
        fb_gemm<1><<<dim3(F_ / 32, D_ / 32), 256, 0, st>>>(p);
        fb_gemm<2><<<dim3(D_ / 32, S_ / 32), 256, 0, st>>>(p);
        return;
    }
    cudaLaunchKernelEx(&cfg, fused_kernel, p, mX, mBre, mBim, mW1, mCre, mCim, mW2, mHn, mOut);
}
```
